```python
import torch

def _softmax(x, axis=-1):
    return torch.softmax(x, dim=axis)

def _gelu(x):
    return torch.nn.functional.gelu(x, approximate='tanh')

def _silu(x):
    return torch.nn.functional.silu(x)

def _sigmoid(x):
    return torch.sigmoid(x)

def _layernorm(x, axis=-1, eps=1e-05):
    m = x.mean(dim=axis, keepdim=True)
    v = x.var(dim=axis, keepdim=True, unbiased=False)
    return (x - m) / torch.sqrt(v + eps)

def _scatter_add(tgt, idx, src, axis=0):
    return tgt.clone().index_add_(axis, idx, src)

def _segment_sum(src, seg, n):
    out = torch.zeros((n,) + src.shape[1:], dtype=src.dtype)
    return out.index_add_(0, seg, src)

def _pad(x, pw):
    flat = tuple((v for pair in reversed(pw) for v in pair))
    return torch.nn.functional.pad(x, flat)
kernel_name = 'concat_heads__softmax_full_mha__memory_aug_recurrent_mem_tr__prompt'

def setup_inputs():

    _w = lambda a: (lambda t: t.to(torch.bfloat16) if t.is_floating_point() else t)(torch.as_tensor(a))

    def _A_setup():
        B, S, D = (1, 2048, 1024)
        return {'x': _w((lambda *s: torch.randn(*s, dtype=torch.bfloat16) * 0.2)(B, S, D)), 'wqkv': _w((lambda *s: torch.randn(*s, dtype=torch.bfloat16) * 0.2)(D, 3 * D)), 'wo': _w((lambda *s: torch.randn(*s, dtype=torch.bfloat16) * 0.05)(D, D))}
    _A_in = _A_setup()

    def _B_setup():
        B, S, Dm = (1, 2048, 1024)
        H, Dh = (32, 128)
        M, seg = (8, 32)
        seg = min(seg, S)
        S = S // seg * seg
        return {'x': _w((lambda *s: torch.randn(*s, dtype=torch.bfloat16) * 0.05)(B, S, Dm)), 'mem0': _w((lambda *s: torch.randn(*s, dtype=torch.bfloat16) * 1.6)(B, M, Dm)), 'Wq': _w((lambda *s: torch.randn(*s, dtype=torch.bfloat16) * 0.8)(Dm, H, Dh) * Dm ** (-0.5)), 'Wk': _w((lambda *s: torch.randn(*s, dtype=torch.bfloat16) * 0.8)(Dm, H, Dh) * Dm ** (-0.5)), 'Wv': _w((lambda *s: torch.randn(*s, dtype=torch.bfloat16) * 1.6)(Dm, H, Dh) * Dm ** (-0.5)), 'Wo': _w((lambda *s: torch.randn(*s, dtype=torch.bfloat16) * 1.6)(H, Dh, Dm) * (H * Dh) ** (-0.5)), 'seg_len': seg}
    _B_in = _B_setup()
    return {'A_x': _A_in['x'], 'A_wqkv': _A_in['wqkv'], 'A_wo': _A_in['wo'], 'B_x': _B_in['x'], 'B_mem0': _B_in['mem0'], 'B_Wq': _B_in['Wq'], 'B_Wk': _B_in['Wk'], 'B_Wv': _B_in['Wv'], 'B_Wo': _B_in['Wo'], 'B_seg_len': _B_in['seg_len']}

def reference(A_x, A_wqkv, A_wo, B_x, B_mem0, B_Wq, B_Wk, B_Wv, B_Wo, B_seg_len):

    def _A_ref(x, wqkv, wo):
        B, S, D = x.shape
        H = 32
        Dh = D // H
        qkv = (lambda x, *d: x.permute(*d))((x @ wqkv).reshape(B, S, 3, H, Dh), 2, 0, 3, 1, 4)
        q, k, v = (qkv[0], qkv[1], qkv[2])
        scale = Dh ** (-0.5)
        scores = torch.einsum('bhqd,bhkd->bhqk', q, k) * scale
        p = _softmax(scores, axis=-1)
        o = torch.einsum('bhqk,bhkd->bhqd', p, v)
        return (lambda x, *d: x.permute(*d))(o, 0, 2, 1, 3).reshape(B, S, D) @ wo

    def _B_ref(x, mem0, Wq, Wk, Wv, Wo, seg_len):
        B, S, Dm = x.shape
        H, Dh = (Wq.shape[1], Wq.shape[2])
        M = mem0.shape[1]
        scale = Dh ** (-0.5)
        n_seg = S // seg_len
        L = M + seg_len
        idx = torch.arange(L)
        mask = (idx[:, None] < M) | (idx[:, None] >= idx[None, :])
        mem = mem0
        outs = []
        for s in range(n_seg):
            xs = x[:, s * seg_len:(s + 1) * seg_len, :].clone()
            h = torch.concatenate([mem, xs], axis=1)
            q = torch.einsum('btd,dhe->bhte', h, Wq)
            k = torch.einsum('btd,dhe->bhte', h, Wk)
            v = torch.einsum('btd,dhe->bhte', h, Wv)
            scores = torch.einsum('bhqe,bhke->bhqk', q, k) * scale
            scores = torch.where(mask[None, None], scores, -1000000000.0)
            p = _softmax(scores, axis=-1)
            o = torch.einsum('bhqk,bhke->bhqe', p, v)
            o = torch.einsum('bhte,hed->btd', o, Wo)
            mem = o[:, :M, :].clone()
            outs.append(o[:, M:, :])
        return torch.concatenate(outs, axis=1)
    a = _A_ref(A_x, A_wqkv, A_wo)
    b = _B_ref(B_x, B_mem0, B_Wq, B_Wk, B_Wv, B_Wo, B_seg_len)
    return torch.concatenate([a, b], axis=-1)
```

```cpp
#include <cuda_runtime.h>
#include <cuda_bf16.h>
#include <cuda.h>
#include <stdint.h>

#define CH_WATCHDOG 1
#define DEVI __device__ __forceinline__
typedef __nv_bfloat16 bf16;

DEVI uint32_t smem_u32(const void* p) { return (uint32_t)__cvta_generic_to_shared(p); }
DEVI void mbar_init(uint32_t b, int c) { asm volatile("mbarrier.init.shared::cta.b64 [%0], %1;" ::"r"(b), "r"(c) : "memory"); }
DEVI void mbar_expect_tx(uint32_t b, uint32_t bytes) {
    asm volatile("mbarrier.arrive.expect_tx.shared::cta.b64 _, [%0], %1;" ::"r"(b), "r"(bytes) : "memory");
}
DEVI void mbar_arrive(uint32_t b) { asm volatile("mbarrier.arrive.shared::cta.b64 _, [%0];" ::"r"(b) : "memory"); }
DEVI bool mbar_try(uint32_t b, uint32_t ph) {
    uint32_t ok;
    asm volatile("{\n.reg .pred p;\nmbarrier.try_wait.parity.shared::cta.b64 p, [%1], %2;\nselp.u32 %0, 1, 0, p;\n}\n"
                 : "=r"(ok) : "r"(b), "r"(ph) : "memory");
    return ok != 0;
}
DEVI void mbar_wait(uint32_t b, uint32_t ph) {
    asm volatile("{\n.reg .pred p;\n.reg .u32 t0, t1;\n"
                 "mbarrier.try_wait.parity.shared::cta.b64 p, [%0], %1;\n@p bra D;\n"
                 "mov.u32 t0, %%clock;\n"
                 "W:\nmbarrier.try_wait.parity.shared::cta.b64 p, [%0], %1;\n@p bra D;\n"
                 "mov.u32 t1, %%clock;\nsub.u32 t1, t1, t0;\nsetp.lt.s32 p, t1, 0x10000000;\n@p bra W;\ntrap;\nD:\n}\n" ::"r"(b), "r"(ph) : "memory");
}
DEVI void fence_mbar_init() { asm volatile("fence.mbarrier_init.release.cluster;" ::: "memory"); }
DEVI void fence_proxy_async() { asm volatile("fence.proxy.async.shared::cta;" ::: "memory"); }
DEVI void tma_load_2d(uint32_t dst, const CUtensorMap* m, int c0, int c1, uint32_t bar) {
    asm volatile("cp.async.bulk.tensor.2d.shared::cluster.global.mbarrier::complete_tx::bytes [%0], [%1, {%3, %4}], [%2];"
                 ::"r"(dst), "l"(m), "r"(bar), "r"(c0), "r"(c1) : "memory");
}
DEVI void tma_store_2d(const CUtensorMap* m, uint32_t src, int c0, int c1) {
    asm volatile("cp.async.bulk.tensor.2d.global.shared::cta.bulk_group [%0, {%2, %3}], [%1];"
                 ::"l"(m), "r"(src), "r"(c0), "r"(c1) : "memory");
}
DEVI void bulk_load(uint32_t dst, const void* src, uint32_t bytes, uint32_t bar) {
    asm volatile("cp.async.bulk.shared::cluster.global.mbarrier::complete_tx::bytes [%0], [%1], %2, [%3];"
                 ::"r"(dst), "l"(src), "r"(bytes), "r"(bar) : "memory");
}
DEVI void bulk_load_last(uint32_t dst, const void* src, uint32_t bytes, uint32_t bar) {
    asm volatile("{\n.reg .b64 pol;\ncreatepolicy.fractional.L2::evict_first.b64 pol, 1.0;\n"
                 "cp.async.bulk.shared::cluster.global.mbarrier::complete_tx::bytes.L2::cache_hint [%0], [%1], %2, [%3], pol;\n}\n"
                 ::"r"(dst), "l"(src), "r"(bytes), "r"(bar) : "memory");
}
DEVI void bulk_store(void* dst, uint32_t src, uint32_t bytes) {
    asm volatile("cp.async.bulk.global.shared::cta.bulk_group [%0], [%1], %2;" ::"l"(dst), "r"(src), "r"(bytes) : "memory");
}
DEVI void bulk_commit() { asm volatile("cp.async.bulk.commit_group;" ::: "memory"); }
DEVI void bulk_wait0() { asm volatile("cp.async.bulk.wait_group 0;" ::: "memory"); }
DEVI void bulk_wait0_read() { asm volatile("cp.async.bulk.wait_group.read 0;" ::: "memory"); }
DEVI void prefetch_tmap(const CUtensorMap* m) { asm volatile("prefetch.tensormap [%0];" ::"l"(m) : "memory"); }
DEVI void named_bar(int id, int n) { asm volatile("bar.sync %0, %1;" ::"r"(id), "r"(n) : "memory"); }
DEVI void pdl_wait() { asm volatile("griddepcontrol.wait;" ::: "memory"); }
DEVI void pdl_launch() { asm volatile("griddepcontrol.launch_dependents;" ::: "memory"); }
DEVI void l2_prefetch(const void* p, uint32_t bytes) { asm volatile("cp.async.bulk.prefetch.L2.global [%0], %1;" ::"l"(p), "r"(bytes) : "memory"); }
DEVI void tma_prefetch_2d(const CUtensorMap* m, int c0, int c1) {
    asm volatile("cp.async.bulk.prefetch.tensor.2d.L2.global [%0, {%1, %2}];" ::"l"(m), "r"(c0), "r"(c1) : "memory");
}
DEVI int chain_role(int by_smid) {
    int cta = blockIdx.x;
    if (by_smid) {
        uint32_t sm;
        asm("mov.u32 %0, %%smid;" : "=r"(sm));
        const int t = sm >> 1;
        if (sm < 64) cta = ((t & 7) * 2 + (t >> 4)) * 4 + ((t >> 3) & 1) * 2 + (sm & 1);
        else if (sm < 120) { const int u = t - 32, q7 = u / 7; cta = (16 + (u - q7 * 7) * 2 + (q7 >> 1)) * 4 + (q7 & 1) * 2 + (sm & 1); }
        else cta = sm < 124 ? sm + 8 : sm - 4;
    }
    return cta;
}
DEVI void wg_fence() { asm volatile("wgmma.fence.sync.aligned;" ::: "memory"); }
DEVI void wg_commit() { asm volatile("wgmma.commit_group.sync.aligned;" ::: "memory"); }
template <int N> DEVI void wg_wait() { asm volatile("wgmma.wait_group.sync.aligned %0;" ::"n"(N) : "memory"); }
DEVI uint64_t make_desc(uint32_t addr, uint32_t lbo, uint32_t sbo, uint32_t swz) {
    return (uint64_t)((addr & 0x3FFFF) >> 4) | ((uint64_t)(lbo >> 4) << 16) | ((uint64_t)(sbo >> 4) << 32) | ((uint64_t)swz << 62);
}
DEVI uint64_t desc_q(uint32_t sq, uint32_t off, uint32_t lbo, uint32_t sbo, uint32_t swz) {
    uint64_t d;
    asm("mov.b64 %0, {%1, %2};" : "=l"(d) : "r"(sq + ((off >> 4) | ((lbo >> 4) << 16))), "r"((sbo >> 4) | (swz << 30)));
    return d;
}
DEVI uint32_t pack_bf16(float lo, float hi) {
    uint32_t r;
    asm("cvt.rn.bf16x2.f32 %0, %1, %2;" : "=r"(r) : "f"(hi), "f"(lo));
    return r;
}
DEVI void stsm4(uint32_t addr, uint32_t r0, uint32_t r1, uint32_t r2, uint32_t r3) {
    asm volatile("stmatrix.sync.aligned.m8n8.x4.shared.b16 [%0], {%1,%2,%3,%4};" ::"r"(addr), "r"(r0), "r"(r1), "r"(r2), "r"(r3) : "memory");
}
DEVI void ldsm4(uint32_t& r0, uint32_t& r1, uint32_t& r2, uint32_t& r3, uint32_t addr) {
    asm volatile("ldmatrix.sync.aligned.m8n8.x4.shared.b16 {%0,%1,%2,%3}, [%4];" : "=r"(r0), "=r"(r1), "=r"(r2), "=r"(r3) : "r"(addr) : "memory");
}
DEVI void ldsm4t(uint32_t& r0, uint32_t& r1, uint32_t& r2, uint32_t& r3, uint32_t addr) {
    asm volatile("ldmatrix.sync.aligned.m8n8.x4.trans.shared.b16 {%0,%1,%2,%3}, [%4];" : "=r"(r0), "=r"(r1), "=r"(r2), "=r"(r3) : "r"(addr) : "memory");
}
DEVI void mma16816(float (&d)[4], uint32_t a0, uint32_t a1, uint32_t a2, uint32_t a3, uint32_t b0, uint32_t b1) {
    asm volatile("mma.sync.aligned.m16n8k16.row.col.f32.bf16.bf16.f32 {%0,%1,%2,%3}, {%4,%5,%6,%7}, {%8,%9}, {%0,%1,%2,%3};"
                 : "+f"(d[0]), "+f"(d[1]), "+f"(d[2]), "+f"(d[3]) : "r"(a0), "r"(a1), "r"(a2), "r"(a3), "r"(b0), "r"(b1));
}
DEVI float ex2(float x) { float y; asm("ex2.approx.ftz.f32 %0, %1;" : "=f"(y) : "f"(x)); return y; }
template <int N> DEVI void fence_regs(float (&d)[N]) {
#pragma unroll
    for (int i = 0; i < N; i++) asm volatile("" : "+f"(d[i])::"memory");
}

#define TLMIN(i)
#define TLMAX(i)
DEVI void wgmma_ss_n192_tb(float (&d)[96], uint64_t adesc, uint64_t bdesc, int scale_d) {
    asm volatile("{\n.reg .pred p;\nsetp.ne.b32 p, %98, 0;\nwgmma.mma_async.sync.aligned.m64n192k16.f32.bf16.bf16 {%0,%1,%2,%3,%4,%5,%6,%7,%8,%9,%10,%11,%12,%13,%14,%15,%16,%17,%18,%19,%20,%21,%22,%23,%24,%25,%26,%27,%28,%29,%30,%31,%32,%33,%34,%35,%36,%37,%38,%39,%40,%41,%42,%43,%44,%45,%46,%47,%48,%49,%50,%51,%52,%53,%54,%55,%56,%57,%58,%59,%60,%61,%62,%63,%64,%65,%66,%67,%68,%69,%70,%71,%72,%73,%74,%75,%76,%77,%78,%79,%80,%81,%82,%83,%84,%85,%86,%87,%88,%89,%90,%91,%92,%93,%94,%95}, %96, %97, p, 1, 1, 0, 1;\n}\n"
        : "+f"(d[0]),"+f"(d[1]),"+f"(d[2]),"+f"(d[3]),"+f"(d[4]),"+f"(d[5]),"+f"(d[6]),"+f"(d[7]),"+f"(d[8]),"+f"(d[9]),"+f"(d[10]),"+f"(d[11]),"+f"(d[12]),"+f"(d[13]),"+f"(d[14]),"+f"(d[15]),"+f"(d[16]),"+f"(d[17]),"+f"(d[18]),"+f"(d[19]),"+f"(d[20]),"+f"(d[21]),"+f"(d[22]),"+f"(d[23]),"+f"(d[24]),"+f"(d[25]),"+f"(d[26]),"+f"(d[27]),"+f"(d[28]),"+f"(d[29]),"+f"(d[30]),"+f"(d[31]),"+f"(d[32]),"+f"(d[33]),"+f"(d[34]),"+f"(d[35]),"+f"(d[36]),"+f"(d[37]),"+f"(d[38]),"+f"(d[39]),"+f"(d[40]),"+f"(d[41]),"+f"(d[42]),"+f"(d[43]),"+f"(d[44]),"+f"(d[45]),"+f"(d[46]),"+f"(d[47]),"+f"(d[48]),"+f"(d[49]),"+f"(d[50]),"+f"(d[51]),"+f"(d[52]),"+f"(d[53]),"+f"(d[54]),"+f"(d[55]),"+f"(d[56]),"+f"(d[57]),"+f"(d[58]),"+f"(d[59]),"+f"(d[60]),"+f"(d[61]),"+f"(d[62]),"+f"(d[63]),"+f"(d[64]),"+f"(d[65]),"+f"(d[66]),"+f"(d[67]),"+f"(d[68]),"+f"(d[69]),"+f"(d[70]),"+f"(d[71]),"+f"(d[72]),"+f"(d[73]),"+f"(d[74]),"+f"(d[75]),"+f"(d[76]),"+f"(d[77]),"+f"(d[78]),"+f"(d[79]),"+f"(d[80]),"+f"(d[81]),"+f"(d[82]),"+f"(d[83]),"+f"(d[84]),"+f"(d[85]),"+f"(d[86]),"+f"(d[87]),"+f"(d[88]),"+f"(d[89]),"+f"(d[90]),"+f"(d[91]),"+f"(d[92]),"+f"(d[93]),"+f"(d[94]),"+f"(d[95])
        : "l"(adesc),"l"(bdesc),"r"(scale_d));
}

DEVI void wgmma_ss_n128_tb(float (&d)[64], uint64_t adesc, uint64_t bdesc, int scale_d) {
    asm volatile("{\n.reg .pred p;\nsetp.ne.b32 p, %66, 0;\nwgmma.mma_async.sync.aligned.m64n128k16.f32.bf16.bf16 {%0,%1,%2,%3,%4,%5,%6,%7,%8,%9,%10,%11,%12,%13,%14,%15,%16,%17,%18,%19,%20,%21,%22,%23,%24,%25,%26,%27,%28,%29,%30,%31,%32,%33,%34,%35,%36,%37,%38,%39,%40,%41,%42,%43,%44,%45,%46,%47,%48,%49,%50,%51,%52,%53,%54,%55,%56,%57,%58,%59,%60,%61,%62,%63}, %64, %65, p, 1, 1, 0, 1;\n}\n"
        : "+f"(d[0]),"+f"(d[1]),"+f"(d[2]),"+f"(d[3]),"+f"(d[4]),"+f"(d[5]),"+f"(d[6]),"+f"(d[7]),"+f"(d[8]),"+f"(d[9]),"+f"(d[10]),"+f"(d[11]),"+f"(d[12]),"+f"(d[13]),"+f"(d[14]),"+f"(d[15]),"+f"(d[16]),"+f"(d[17]),"+f"(d[18]),"+f"(d[19]),"+f"(d[20]),"+f"(d[21]),"+f"(d[22]),"+f"(d[23]),"+f"(d[24]),"+f"(d[25]),"+f"(d[26]),"+f"(d[27]),"+f"(d[28]),"+f"(d[29]),"+f"(d[30]),"+f"(d[31]),"+f"(d[32]),"+f"(d[33]),"+f"(d[34]),"+f"(d[35]),"+f"(d[36]),"+f"(d[37]),"+f"(d[38]),"+f"(d[39]),"+f"(d[40]),"+f"(d[41]),"+f"(d[42]),"+f"(d[43]),"+f"(d[44]),"+f"(d[45]),"+f"(d[46]),"+f"(d[47]),"+f"(d[48]),"+f"(d[49]),"+f"(d[50]),"+f"(d[51]),"+f"(d[52]),"+f"(d[53]),"+f"(d[54]),"+f"(d[55]),"+f"(d[56]),"+f"(d[57]),"+f"(d[58]),"+f"(d[59]),"+f"(d[60]),"+f"(d[61]),"+f"(d[62]),"+f"(d[63])
        : "l"(adesc),"l"(bdesc),"r"(scale_d));
}

DEVI void wgmma_ss_n64(float (&d)[32], uint64_t adesc, uint64_t bdesc, int scale_d) {
    asm volatile("{\n.reg .pred p;\nsetp.ne.b32 p, %34, 0;\nwgmma.mma_async.sync.aligned.m64n64k16.f32.bf16.bf16 {%0,%1,%2,%3,%4,%5,%6,%7,%8,%9,%10,%11,%12,%13,%14,%15,%16,%17,%18,%19,%20,%21,%22,%23,%24,%25,%26,%27,%28,%29,%30,%31}, %32, %33, p, 1, 1, 0, 0;\n}\n"
        : "+f"(d[0]),"+f"(d[1]),"+f"(d[2]),"+f"(d[3]),"+f"(d[4]),"+f"(d[5]),"+f"(d[6]),"+f"(d[7]),"+f"(d[8]),"+f"(d[9]),"+f"(d[10]),"+f"(d[11]),"+f"(d[12]),"+f"(d[13]),"+f"(d[14]),"+f"(d[15]),"+f"(d[16]),"+f"(d[17]),"+f"(d[18]),"+f"(d[19]),"+f"(d[20]),"+f"(d[21]),"+f"(d[22]),"+f"(d[23]),"+f"(d[24]),"+f"(d[25]),"+f"(d[26]),"+f"(d[27]),"+f"(d[28]),"+f"(d[29]),"+f"(d[30]),"+f"(d[31])
        : "l"(adesc),"l"(bdesc),"r"(scale_d));
}

DEVI void wgmma_rs_n40_tb(float (&d)[20], uint32_t a0, uint32_t a1, uint32_t a2, uint32_t a3, uint64_t bdesc, int scale_d) {
    asm volatile("{\n.reg .pred p;\nsetp.ne.b32 p, %25, 0;\nwgmma.mma_async.sync.aligned.m64n40k16.f32.bf16.bf16 {%0,%1,%2,%3,%4,%5,%6,%7,%8,%9,%10,%11,%12,%13,%14,%15,%16,%17,%18,%19}, {%20,%21,%22,%23}, %24, p, 1, 1, 1;\n}\n"
        : "+f"(d[0]),"+f"(d[1]),"+f"(d[2]),"+f"(d[3]),"+f"(d[4]),"+f"(d[5]),"+f"(d[6]),"+f"(d[7]),"+f"(d[8]),"+f"(d[9]),"+f"(d[10]),"+f"(d[11]),"+f"(d[12]),"+f"(d[13]),"+f"(d[14]),"+f"(d[15]),"+f"(d[16]),"+f"(d[17]),"+f"(d[18]),"+f"(d[19])
        : "r"(a0),"r"(a1),"r"(a2),"r"(a3),"l"(bdesc),"r"(scale_d));
}

DEVI void wgmma_rs_n32(float (&d)[16], uint32_t a0, uint32_t a1, uint32_t a2, uint32_t a3, uint64_t bdesc, int scale_d) {
    asm volatile("{\n.reg .pred p;\nsetp.ne.b32 p, %21, 0;\nwgmma.mma_async.sync.aligned.m64n32k16.f32.bf16.bf16 {%0,%1,%2,%3,%4,%5,%6,%7,%8,%9,%10,%11,%12,%13,%14,%15}, {%16,%17,%18,%19}, %20, p, 1, 1, 0;\n}\n"
        : "+f"(d[0]),"+f"(d[1]),"+f"(d[2]),"+f"(d[3]),"+f"(d[4]),"+f"(d[5]),"+f"(d[6]),"+f"(d[7]),"+f"(d[8]),"+f"(d[9]),"+f"(d[10]),"+f"(d[11]),"+f"(d[12]),"+f"(d[13]),"+f"(d[14]),"+f"(d[15])
        : "r"(a0),"r"(a1),"r"(a2),"r"(a3),"l"(bdesc),"r"(scale_d));
}

DEVI void wgmma_ss_n32_ta(float (&d)[16], uint64_t adesc, uint64_t bdesc, int scale_d) {
    asm volatile("{\n.reg .pred p;\nsetp.ne.b32 p, %18, 0;\nwgmma.mma_async.sync.aligned.m64n32k16.f32.bf16.bf16 {%0,%1,%2,%3,%4,%5,%6,%7,%8,%9,%10,%11,%12,%13,%14,%15}, %16, %17, p, 1, 1, 1, 0;\n}\n"
        : "+f"(d[0]),"+f"(d[1]),"+f"(d[2]),"+f"(d[3]),"+f"(d[4]),"+f"(d[5]),"+f"(d[6]),"+f"(d[7]),"+f"(d[8]),"+f"(d[9]),"+f"(d[10]),"+f"(d[11]),"+f"(d[12]),"+f"(d[13]),"+f"(d[14]),"+f"(d[15])
        : "l"(adesc),"l"(bdesc),"r"(scale_d));
}

#define SEQ 2048
__device__ __align__(1024) bf16 g_qkvA[96 * SEQ * 32];
__device__ __align__(1024) bf16 g_oA[SEQ * 1024];
__device__ __align__(1024) bf16 g_oB[SEQ * 4096];

DEVI size_t qkv_off(int hh, int blk) {
    return hh < 32 ? ((size_t)hh * 16 + blk) * 4096 : (size_t)32 * SEQ * 32 + (((size_t)(hh & 31) * 16 + blk) * 2 + (hh >= 64)) * 4096;
}
#define K1_STAGE (32768 + 24576)
#define K1_SMEM (4 * K1_STAGE + 128)
__global__ void __launch_bounds__(384, 1)
k1_qkv_gemm(const __grid_constant__ CUtensorMap tmA, const __grid_constant__ CUtensorMap tmB, uint4* __restrict__ clr, int nclr, uint4* __restrict__ box) {
    extern __shared__ __align__(1024) unsigned char smem[];
    const uint32_t sb = smem_u32(smem);
    const uint32_t bar_full = sb + 4 * K1_STAGE, bar_empty = bar_full + 32;
    const int tid = threadIdx.x, warp = tid >> 5, lane = tid & 31;
    const int g = blockIdx.x >> 4, i = blockIdx.x & 15;
    const int mt = (g >> 2) * 4 + (i >> 2), nt = (g & 3) * 4 + (i & 3);
    if (tid == 0) {
        for (int s = 0; s < 4; s++) { mbar_init(bar_full + 8 * s, 1); mbar_init(bar_empty + 8 * s, 8); }
        fence_mbar_init();
    }
    __syncthreads();
    if (__shfl_sync(~0u, warp, 0) >= 8) {
        asm volatile("setmaxnreg.dec.sync.aligned.u32 24;");
        pdl_launch();
        if (tid == 256) { prefetch_tmap(&tmA); prefetch_tmap(&tmB); }
        if (tid >= 288) {
            for (int i = blockIdx.x * 96 + tid - 288; i < nclr; i += 128 * 96) clr[i] = make_uint4(~0u, ~0u, ~0u, ~0u);
            if (tid < 292) box[((blockIdx.x >> 1) * 65536 + (blockIdx.x & 1) * 8192 + (tid & 2) * 2048) / 16 + (tid & 1)] = make_uint4(~0u, ~0u, ~0u, ~0u);
        }
        if (tid == 256) {
            TLMIN(0);
            for (int k = 0; k < 16; k++) {
                const int s = k & 3;
                if (k >= 4) mbar_wait(bar_empty + 8 * s, ((k >> 2) - 1) & 1);
                const uint32_t st = sb + s * K1_STAGE;
                mbar_expect_tx(bar_full + 8 * s, K1_STAGE);
                tma_load_2d(st, &tmA, k * 64, mt * 256, bar_full + 8 * s);
#pragma unroll
                for (int j = 0; j < 3; j++) tma_load_2d(st + 32768 + j * 8192, &tmB, nt * 192 + j * 64, k * 64, bar_full + 8 * s);
            }
        }
    } else {
        asm volatile("setmaxnreg.inc.sync.aligned.u32 240;");
        const int wg = warp >> 2;
        float acc0[96], acc1[96];
        for (int k = 0; k < 16; k++) {
            const int s = k & 3;
            mbar_wait(bar_full + 8 * s, (k >> 2) & 1);
            const uint32_t st = sb + s * K1_STAGE;
            wg_fence();
#pragma unroll
            for (int kk = 0; kk < 4; kk++) {
                uint64_t ad = make_desc(st + wg * 16384 + kk * 32, 16, 1024, 1);
                uint64_t bd = make_desc(st + 32768 + kk * 2048, 8192, 1024, 1);
                wgmma_ss_n192_tb(acc0, ad, bd, (k | kk) != 0);
                wgmma_ss_n192_tb(acc1, ad + (8192 >> 4), bd, (k | kk) != 0);
            }
            wg_commit();
            if (k > 0) {
                wg_wait<1>();
                if (lane == 0) mbar_arrive(bar_empty + 8 * ((k - 1) & 3));
            }
        }
        wg_wait<0>();
        fence_regs(acc0);
        fence_regs(acc1);
        if ((tid & 127) == 0) TLMAX(12);
        const int w4 = warp & 3;
        const int row = w4 * 16 + (lane & 7) + ((lane >> 3) & 1) * 8;
#pragma unroll
        for (int c = 0; c < 6; c++) {
            const uint32_t cb = sb + (c >> 1) * K1_STAGE + wg * 16384 + (c & 1) * 8192;
            if (nt * 6 + c < 32) {
                const float cs = 0.17677669529663687f * 1.4426950408889634f;
#pragma unroll
                for (int t = 0; t < 16; t++) { acc0[c * 16 + t] *= cs; acc1[c * 16 + t] *= cs; }
            }
#pragma unroll
            for (int j = 0; j < 2; j++) {
                const int t = c * 4 + j * 2;
                const int chunk = j * 2 + (lane >> 4);
                const uint32_t ad = cb + row * 64 + ((chunk ^ ((row >> 1) & 3)) << 4);
                stsm4(ad, pack_bf16(acc0[t * 4 + 0], acc0[t * 4 + 1]), pack_bf16(acc0[t * 4 + 2], acc0[t * 4 + 3]),
                      pack_bf16(acc0[t * 4 + 4], acc0[t * 4 + 5]), pack_bf16(acc0[t * 4 + 6], acc0[t * 4 + 7]));
                stsm4(ad + 4096, pack_bf16(acc1[t * 4 + 0], acc1[t * 4 + 1]), pack_bf16(acc1[t * 4 + 2], acc1[t * 4 + 3]),
                      pack_bf16(acc1[t * 4 + 4], acc1[t * 4 + 5]), pack_bf16(acc1[t * 4 + 6], acc1[t * 4 + 7]));
            }
            if (c & 1) {
                fence_proxy_async();
                named_bar(1 + wg, 128);
                if ((tid & 127) == 0) {
                    bulk_store(g_qkvA + qkv_off(nt * 6 + c - 1, mt * 2 + wg), cb - 8192, 8192);
                    bulk_store(g_qkvA + qkv_off(nt * 6 + c, mt * 2 + wg), cb, 8192);
                    bulk_commit();
                }
            }
        }
        if ((tid & 127) == 0) { bulk_wait0(); TLMAX(1); }
    }
}

#define EVF 0
#define PF_WO 1
#define PF_AT 18
#define AT_ST 4
#define AT_Q (AT_ST * 16384)
#define AT_M (AT_Q + 32768)
#define AT_ONE (AT_M + 8192)
#define AT_SEL (AT_ONE + 1024)
#define AT_BAR (AT_SEL + 2048)
#define AT_SMEM (AT_BAR + 128)
DEVI uint32_t vmax3_u16x2(uint32_t a, uint32_t b, uint32_t c) { return __vimax3_u16x2(a, b, c); }
DEVI float ex2_fma(float x) {
    const float t = __saturatef(fmaf(x, 0.004f, 0.5f));
    const float r = fmaf(t, 250.f, 12582912.f - 125.f);
    const float f = fmaf(t, 250.f, (12582912.f - 125.f) - r);
    float p = fmaf(f, 0.0551716648f, 0.24261114f);
    p = fmaf(p, f, 0.693260968f);
    p = fmaf(p, f, 0.999928057f);
    return __uint_as_float(__float_as_uint(p) + (__float_as_uint(r) << 23));
}
#define AT_POLY 0
#define AT_BLK 4
DEVI void bb_split(uint32_t zero) { asm volatile("{\n.reg .pred q;\nsetp.eq.u32 q, %0, 0;\n@q bra.uni S;\ntrap;\nS:\n}\n" ::"r"(zero) : "memory"); }
struct AttnState { float m0, m1; uint32_t maddr, zero; };
DEVI void split3(float m, uint32_t& hi_lo, uint32_t& lo2) {
    const float n = -m;
    const float t0 = __uint_as_float(__float_as_uint(n) & 0xFFFF0000u);
    const float r = n - t0;
    const float t1 = __uint_as_float(__float_as_uint(r) & 0xFFFF0000u);
    const float t2 = r - t1;
    hi_lo = (__float_as_uint(t0) >> 16) | (__float_as_uint(t1) & 0xFFFF0000u);
    lo2 = __float_as_uint(t2) >> 16;
}
template <bool FIRST>
DEVI void attn_probs(float (&sc)[32], uint32_t (&p)[16], float (&o)[20], AttnState& st) {
    bool redo = FIRST;
    if (!FIRST) {
#pragma unroll
        for (int t = 0; t < 16; t++) {
            if (AT_POLY && t > 0 && t % AT_BLK == 0) { bb_split(st.zero); asm volatile("" : "+f"(sc[2 * t]), "+f"(sc[2 * t + 1]), "+f"(sc[2 * t + 2]), "+f"(sc[2 * t + 3]), "+f"(sc[(2 * t + 4) & 31]), "+f"(sc[(2 * t + 5) & 31]), "+f"(sc[(2 * t + 6) & 31]), "+f"(sc[(2 * t + 7) & 31])); }
            p[t] = pack_bf16(ex2(sc[2 * t]), ((AT_POLY >> t) & 1) ? ex2_fma(sc[2 * t + 1]) : ex2(sc[2 * t + 1]));
        }
        uint32_t x = vmax3_u16x2(vmax3_u16x2(p[0], p[1], p[2]), vmax3_u16x2(p[3], p[4], p[5]), vmax3_u16x2(p[6], p[7], p[8]));
        uint32_t y = vmax3_u16x2(vmax3_u16x2(p[9], p[10], p[11]), vmax3_u16x2(p[12], p[13], p[14]), p[15]);
        x = vmax3_u16x2(x, y, 0x45804580u);
        redo = __any_sync(~0u, x != 0x45804580u);
    }
    if (redo) {
        float x0 = fmaxf(sc[0], sc[1]), x1 = fmaxf(sc[2], sc[3]);
#pragma unroll
        for (int t = 1; t < 8; t++) {
            x0 = fmaxf(x0, fmaxf(sc[4 * t], sc[4 * t + 1]));
            x1 = fmaxf(x1, fmaxf(sc[4 * t + 2], sc[4 * t + 3]));
        }
        x0 = fmaxf(x0, __shfl_xor_sync(~0u, x0, 1)); x1 = fmaxf(x1, __shfl_xor_sync(~0u, x1, 1));
        x0 = fmaxf(x0, __shfl_xor_sync(~0u, x0, 2)); x1 = fmaxf(x1, __shfl_xor_sync(~0u, x1, 2));
        if (!FIRST) { x0 = fmaxf(x0, 0.f); x1 = fmaxf(x1, 0.f); }
        const float n0 = st.m0 + x0, n1 = st.m1 + x1;
        const float d0 = n0 - st.m0, d1 = n1 - st.m1;
        st.m0 = n0; st.m1 = n1;
        {
            uint32_t a, b;
            split3((threadIdx.x & 1) ? n1 : n0, a, b);
            asm volatile("st.shared.u32 [%0], %1;" ::"r"(st.maddr), "r"((threadIdx.x & 2) ? b : a) : "memory");
            fence_proxy_async();
        }
#pragma unroll
        for (int t = 0; t < 8; t++) {
            p[2 * t] = pack_bf16(ex2(sc[4 * t] - d0), ex2(sc[4 * t + 1] - d0));
            p[2 * t + 1] = pack_bf16(ex2(sc[4 * t + 2] - d1), ex2(sc[4 * t + 3] - d1));
        }
        if (!FIRST) {
            const float a0 = ex2(-d0), a1 = ex2(-d1);
#pragma unroll
            for (int t = 0; t < 5; t++) { o[4 * t] *= a0; o[4 * t + 1] *= a0; o[4 * t + 2] *= a1; o[4 * t + 3] *= a1; }
        }
    }
}
__global__ void __launch_bounds__(512, 1)
k3_attn(const __grid_constant__ CUtensorMap tmWq, const __grid_constant__ CUtensorMap tmWk, const __grid_constant__ CUtensorMap tmWv,
        const __grid_constant__ CUtensorMap tmWo, const char* xb, int by_smid) {
    extern __shared__ __align__(1024) unsigned char smem[];
    const uint32_t sb = smem_u32(smem);
    const uint32_t bar_full = sb + AT_BAR, bar_empty = bar_full + 8 * AT_ST, bar_q = bar_empty + 8 * AT_ST;
    const int tid = threadIdx.x, warp = (tid >> 5) & 3, lane = tid & 31;
    const int wg = __shfl_sync(~0u, tid >> 7, 0);
    const int h = blockIdx.x >> 2, q0 = (blockIdx.x & 3) * 512;
    const bf16* KVg = g_qkvA + qkv_off(32 + h, 0);
    if (tid == 0) {
        for (int s = 0; s < AT_ST; s++) { mbar_init(bar_full + 8 * s, 1); mbar_init(bar_empty + 8 * s, 16); }
        mbar_init(bar_q, 1);
        fence_mbar_init();
        pdl_wait();
        pdl_launch();
        TLMIN(2);
        mbar_expect_tx(bar_q, 32768);
        if (EVF) bulk_load_last(sb + AT_Q, g_qkvA + ((size_t)h * SEQ + q0) * 32, 32768, bar_q);
        else bulk_load(sb + AT_Q, g_qkvA + ((size_t)h * SEQ + q0) * 32, 32768, bar_q);
        for (int s = 0; s < AT_ST; s++) {
            mbar_expect_tx(bar_full + 8 * s, 16384);
            bulk_load(sb + s * 16384, KVg + s * 8192, 16384, bar_full + 8 * s);
        }
    }
    ((uint4*)(smem + AT_M))[tid] = make_uint4(0u, 0u, 0u, 0u);
    if (tid < 128) ((uint2*)(smem + AT_ONE))[tid] = make_uint2(0x3F803F80u, 0x3F803F80u);
    ((uint32_t*)(smem + AT_SEL))[tid] = (tid & 3) ? 0u : ((tid & 32) ? 0x00003F80u : 0x3F803F80u);
    fence_proxy_async();
    __syncthreads();
    const uint32_t sq = sb >> 4;
    const uint64_t dsel = make_desc(sb + AT_SEL, 128, 256, 0), dm = make_desc(sb + AT_M + wg * 2048, 128, 256, 0);
    float o[20], sc[32];
    uint32_t p[16];
    AttnState st;
    st.maddr = sb + AT_M + wg * 2048 + (warp * 2 + (lane & 1)) * 256 + ((lane >> 1) & 1) * 128 + (lane >> 2) * 16;
    st.zero = by_smid >> 8;
    mbar_wait(bar_q, 0);
#pragma unroll 1
    for (int item = 0; item < 2; item++) {
        const uint64_t dq0 = make_desc(sb + AT_Q + item * 16384 + wg * 4096, 16, 512, 2), dq1 = dq0 + 2;
#pragma unroll
        for (int i = 0; i < 20; i++) o[i] = 0.f;
        st.m0 = st.m1 = 0.f;
        mbar_wait(bar_full, 0);
        wg_fence();
        wgmma_ss_n64(sc, dq0, make_desc(sb, 16, 512, 2), 0);
        wgmma_ss_n64(sc, dq1, make_desc(sb + 32, 16, 512, 2), 1);
        wg_commit();
        wg_wait<0>();
        fence_regs(sc);
        attn_probs<true>(sc, p, o, st);
#define AT_TILE(u, LAST) do { \
            const uint32_t stv = ((u) >> 1) * 16384 + 8192 + ((u) & 1) * 4096; \
            const uint32_t stk = ((((u) + 1) >> 1) & 3) * 16384 + (((u) + 1) & 1) * 4096; \
            if (((u) & 1) && !(LAST)) mbar_wait(bar_full + 8 * ((((u) + 1) >> 1) & 3), (g + ((u) == 7)) & 1); \
            wg_fence(); \
            _Pragma("unroll") for (int kk = 0; kk < 4; kk++) \
                wgmma_rs_n40_tb(o, p[4 * kk], p[4 * kk + 1], p[4 * kk + 2], p[4 * kk + 3], \
                                desc_q(sq, stv + kk * 1024, AT_ONE - (stv + kk * 1024), 512, 2), 1); \
            if (!(LAST)) { \
                wgmma_ss_n64(sc, dq0, desc_q(sq, stk, 16, 512, 2), 0); \
                wgmma_ss_n64(sc, dq1, desc_q(sq, stk + 32, 16, 512, 2), 1); \
                wgmma_ss_n64(sc, dm, dsel, 1); \
            } \
            wg_commit(); \
            if ((u) & 1) { \
                  \
                const int rs = (((u) >> 1) + 3) & 3, nb = item * 16 + 4 * g + ((u) >> 1) + 3; \
                if (tid == 0 && nb >= 4 && nb < 32) { \
                    mbar_wait(bar_empty + 8 * rs, ((nb >> 2) - 1) & 1); \
                    mbar_expect_tx(bar_full + 8 * rs, 16384); \
                    if (EVF && nb >= 16) bulk_load_last(sb + rs * 16384, KVg + (nb & 15) * 8192, 16384, bar_full + 8 * rs); \
                    else bulk_load(sb + rs * 16384, KVg + (nb & 15) * 8192, 16384, bar_full + 8 * rs); \
                } \
                if (tid == 128 && nb >= PF_AT && nb < PF_AT + 8) {     \
                    const int i = nb - PF_AT, r = chain_role(by_smid); \
                    if (r < 128) { \
                        const int wc = (r >> 2) * 128 + (r & 1) * 64, wr = (r & 2) * 256 + i * 64; \
                        tma_prefetch_2d(&tmWq, wc, wr); tma_prefetch_2d(&tmWk, wc, wr); tma_prefetch_2d(&tmWv, wc, wr); \
                        if (PF_WO) tma_prefetch_2d(&tmWo, (r & 3) * 256 + (i >> 1) * 64, (r >> 2) * 128 + (i & 1) * 64); \
                    } \
                    if (i < 2) l2_prefetch(xb + (blockIdx.x * 2 + i) * 16384, 16384); \
                } \
                __syncwarp(); \
            } \
            wg_wait<0>(); \
            fence_regs(sc); fence_regs(o); \
            if (((u) & 1) && lane == 0) mbar_arrive(bar_empty + 8 * ((u) >> 1)); \
            if (!(LAST)) attn_probs<false>(sc, p, o, st); \
        } while (0)
#pragma unroll 1
        for (int g = 0; g < 4; g++) {
            AT_TILE(0, false); AT_TILE(1, false); AT_TILE(2, false); AT_TILE(3, false);
            AT_TILE(4, false); AT_TILE(5, false); AT_TILE(6, false);
            if (g < 3) AT_TILE(7, false); else AT_TILE(7, true);
        }
        const float i0 = 1.f / o[16], i1 = 1.f / o[18];
        const int r0 = q0 + item * 256 + wg * 64 + warp * 16 + (lane >> 2);
        uint32_t* og = (uint32_t*)(g_oA + (size_t)r0 * 1024 + h * 32) + (lane & 3);
#pragma unroll
        for (int t = 0; t < 4; t++) {
            og[t * 4] = pack_bf16(o[4 * t] * i0, o[4 * t + 1] * i0);
            og[t * 4 + 8 * 512] = pack_bf16(o[4 * t + 2] * i1, o[4 * t + 3] * i1);
        }
    }
    if ((tid & 127) == 0) { TLMAX(3); TLMIN(8); }
}

#define K4_ST 6
#define K4_STAGE 32768
#define K4_SMEM (K4_ST * K4_STAGE + 32768 + 128)
DEVI void out_gemm(const CUtensorMap* tmA, const CUtensorMap* tmB, const CUtensorMap* tmOut, int nk, int col0, int t0, int tstep, uint32_t sb) {
    const uint32_t epi = sb + K4_ST * K4_STAGE;
    const uint32_t bar_full = epi + 32768, bar_empty = bar_full + 8 * K4_ST;
    const int tid = threadIdx.x, warp = tid >> 5, lane = tid & 31;
    if (tid == 0) {
        for (int s = 0; s < K4_ST; s++) { mbar_init(bar_full + 8 * s, 1); mbar_init(bar_empty + 8 * s, 8); }
        fence_mbar_init();
    }
    __syncthreads();
    if (warp == 8) {
        if (lane == 0) {
            prefetch_tmap(tmA); prefetch_tmap(tmB);
            pdl_wait();
            if (col0) TLMIN(6);
            int s = 0, ph = 1;
            for (int t = t0; t < 128; t += tstep) {
                const int g = t >> 4, i = t & 15;
                const int mt = (g >> 1) * 4 + (i >> 2), nt = (g & 1) * 4 + (i & 3);
                for (int k = 0; k < nk; k++) {
                    mbar_wait(bar_empty + 8 * s, ph);
                    const uint32_t st = sb + s * K4_STAGE;
                    mbar_expect_tx(bar_full + 8 * s, K4_STAGE);
                    tma_load_2d(st, tmA, k * 64, mt * 128, bar_full + 8 * s);
                    tma_load_2d(st + 16384, tmB, nt * 128, k * 64, bar_full + 8 * s);
                    tma_load_2d(st + 16384 + 8192, tmB, nt * 128 + 64, k * 64, bar_full + 8 * s);
                    if (++s == K4_ST) { s = 0; ph ^= 1; }
                }
            }
        }
    } else if (warp < 8) {
        const int wg = warp >> 2;
        int s = 0, ph = 0;
        for (int t = t0; t < 128; t += tstep) {
            const int g = t >> 4, i = t & 15;
            const int mt = (g >> 1) * 4 + (i >> 2), nt = (g & 1) * 4 + (i & 3);
            float acc[64];
            int ps = 0;
            for (int k = 0; k < nk; k++) {
                mbar_wait(bar_full + 8 * s, ph);
                const uint32_t sq = (sb + s * K4_STAGE) >> 4;
                wg_fence();
#pragma unroll
                for (int kk = 0; kk < 4; kk++)
                    wgmma_ss_n128_tb(acc, desc_q(sq + wg * 512, kk * 32, 16, 1024, 1), desc_q(sq, 16384 + kk * 2048, 8192, 1024, 1), (k | kk) != 0);
                wg_commit();
                if (k > 0) {
                    wg_wait<1>();
                    if (lane == 0) mbar_arrive(bar_empty + 8 * ps);
                }
                ps = s;
                if (++s == K4_ST) { s = 0; ph ^= 1; }
            }
            wg_wait<0>();
            fence_regs(acc);
            if (col0 && (tid & 127) == 0) TLMAX(14);
            if (lane == 0) mbar_arrive(bar_empty + 8 * ps);
            if (t != t0) {
                if ((tid & 127) == 0) bulk_wait0_read();
                named_bar(1 + wg, 128);
            }
            const int w4 = warp & 3;
            const int row = w4 * 16 + (lane & 7) + ((lane >> 3) & 1) * 8;
#pragma unroll
            for (int j = 0; j < 8; j++) {
                const int u = j * 2;
                const int chunk = (j & 3) * 2 + (lane >> 4);
                stsm4(epi + wg * 16384 + (j >> 2) * 8192 + row * 128 + ((chunk ^ (row & 7)) << 4),
                      pack_bf16(acc[u * 4 + 0], acc[u * 4 + 1]), pack_bf16(acc[u * 4 + 2], acc[u * 4 + 3]),
                      pack_bf16(acc[u * 4 + 4], acc[u * 4 + 5]), pack_bf16(acc[u * 4 + 6], acc[u * 4 + 7]));
            }
            fence_proxy_async();
            named_bar(1 + wg, 128);
            if ((tid & 127) == 0) {
                tma_store_2d(tmOut, epi + wg * 16384, col0 + nt * 128, mt * 128 + wg * 64);
                tma_store_2d(tmOut, epi + wg * 16384 + 8192, col0 + nt * 128 + 64, mt * 128 + wg * 64);
                bulk_commit();
            }
        }
        if ((tid & 127) == 0) { bulk_wait0(); TLMAX(col0 ? 7 : 9); }
    }
}
__global__ void __launch_bounds__(288, 1)
k4_out_gemm(const __grid_constant__ CUtensorMap tmA, const __grid_constant__ CUtensorMap tmB, const __grid_constant__ CUtensorMap tmOut) {
    extern __shared__ __align__(1024) unsigned char smem[];
    out_gemm(&tmA, &tmB, &tmOut, 64, 1024, blockIdx.x, 128, smem_u32(smem));
}

#define NSEG 64
#define NRK_QK 24
#define CFG 0
#define NRK_V (CFG ? 24 : 16)
#define NSLOT 4
#define SENT 0xFFFFFFFFu
#define BOX(i, slot, page) (((i) >> 1) * 65536 + (slot) * 16384 + ((i) & 1) * 8192 + (page) * 4096)
#define G1_OFF 0
#define G2_OFF (G1_OFF + 64 * 65536)
#define GF_OFF (G2_OFF + 2 * 65536)
#define GT_OFF (GF_OFF + 4096)
#define G0_OFF (GT_OFF + 4096)
#define G0_SLOT (128 * 3072)
#define GX_OFF (G0_OFF + NSLOT * G0_SLOT)
#define GX_SLOT (32 * 24576)
#define CB_CLEAR_OFF G2_OFF
#define CB_CLEAR (G0_OFF - G2_OFF)
struct ChainBuf { unsigned char b[GX_OFF + NSLOT * GX_SLOT + 65536]; };
__device__ __align__(1024) ChainBuf g_cb;
__device__ int g_done, g_fail;
#define CH_GRID 129
#define WD_LIMIT 400000000ll
#define PROF(i)
#define PROF_DUMP()
#define CALIB(i)

#define CS_WO 0
#define CS_WS (CS_WO + 65536)
#define WS_BYTES ((2 * (32 - NRK_QK) + (32 - NRK_V)) * 2048)
#define CS_MEM (CS_WS + WS_BYTES)
#define CS_FF (CS_MEM + 8192)
#define CS_XS (CS_FF + 2048)
#define CS_STG CS_XS
#define CS_KX (CS_XS + 32768)
#define CS_QX (CS_KX + 8192)
#define CS_V0 (CS_QX + 2048)
#define CS_XP (CS_V0 + 8192)
#define CS_V1 (CS_XP + 12288)
#define CS_VX(t) (((t) & 1) ? CS_V1 : CS_V0)
#define CS_QF (CS_V1 + 8192)
#define CS_KF (CS_QF + 2048)
#define CS_VF (CS_KF + 2048)
#define CS_OM (CS_VF + 2048)
#define CS_SX (CS_OM + 2048)
#define CS_RED (CS_SX + 7168)
#define CS_BAR (CS_RED + 1024)
#define CS_PROF (CS_BAR + 256)
#define CH_SMEM (CS_PROF + 1024)
#define CH_SMEM_ALL (CH_SMEM > K4_SMEM ? CH_SMEM : K4_SMEM)

DEVI uint4 ldg_poll4(const void* p) {
    uint4 v;
    asm volatile("ld.relaxed.gpu.global.v4.u32 {%0,%1,%2,%3}, [%4];" : "=r"(v.x), "=r"(v.y), "=r"(v.z), "=r"(v.w) : "l"(p) : "memory");
    return v;
}
DEVI uint2 ldg_poll2(const void* p) {
    uint2 v;
    asm volatile("ld.relaxed.gpu.global.v2.u32 {%0,%1}, [%2];" : "=r"(v.x), "=r"(v.y) : "l"(p) : "memory");
    return v;
}
DEVI void stg_pub4(void* p, uint32_t a, uint32_t b, uint32_t c, uint32_t d) {
    asm volatile("st.relaxed.gpu.global.v4.u32 [%0], {%1,%2,%3,%4};" ::"l"(p), "r"(a), "r"(b), "r"(c), "r"(d) : "memory");
}
DEVI void stg_pub2(void* p, uint32_t a, uint32_t b) {
    asm volatile("st.relaxed.gpu.global.v2.u32 [%0], {%1,%2};" ::"l"(p), "r"(a), "r"(b) : "memory");
}
DEVI void stg_pub1(void* p, uint32_t a) { asm volatile("st.relaxed.gpu.global.u32 [%0], %1;" ::"l"(p), "r"(a) : "memory"); }
DEVI void sched_fence(uint32_t zero) {
    asm volatile("{\n.reg .pred q;\n.reg .u32 t;\nL:\nmov.u32 t, %%clock;\nand.b32 t, t, %0;\nsetp.ne.u32 q, t, 0;\n@q bra.uni L;\n}\n" ::"r"(zero) : "memory");
}
DEVI int tid_now() { int t; asm volatile("mov.u32 %0, %%tid.x;" : "=r"(t)); return t; }
DEVI uint32_t launder(uint32_t x) { asm volatile("" : "+r"(x)); return x; }
DEVI uint32_t hadd2(uint32_t a, uint32_t b) {
    uint32_t r;
    asm("add.rn.bf16x2 %0, %1, %2;" : "=r"(r) : "r"(a), "r"(b));
    return r;
}
DEVI void sts32(uint32_t a, uint32_t v) { asm volatile("st.shared.u32 [%0], %1;" ::"r"(a), "r"(v) : "memory"); }
DEVI void sts128(uint32_t a, uint32_t x, uint32_t y, uint32_t z, uint32_t w) {
    asm volatile("st.shared.v4.u32 [%0], {%1,%2,%3,%4};" ::"r"(a), "r"(x), "r"(y), "r"(z), "r"(w) : "memory");
}
DEVI float4 lds128f(uint32_t a) {
    float4 v;
    asm volatile("ld.shared.v4.f32 {%0,%1,%2,%3}, [%4];" : "=f"(v.x), "=f"(v.y), "=f"(v.z), "=f"(v.w) : "r"(a) : "memory");
    return v;
}
DEVI float2 lds64f(uint32_t a) {
    float2 v;
    asm volatile("ld.shared.v2.f32 {%0,%1}, [%2];" : "=f"(v.x), "=f"(v.y) : "r"(a) : "memory");
    return v;
}
DEVI void bar_arrive(int id, int n) { asm volatile("bar.arrive %0, %1;" ::"r"(id), "r"(n) : "memory"); }
DEVI void mma1688(float (&d)[4], uint32_t a0, uint32_t a1, uint32_t b0) {
    asm volatile("mma.sync.aligned.m16n8k8.row.col.f32.bf16.bf16.f32 {%0,%1,%2,%3}, {%4,%5}, {%6}, {%0,%1,%2,%3};"
                 : "+f"(d[0]), "+f"(d[1]), "+f"(d[2]), "+f"(d[3]) : "r"(a0), "r"(a1), "r"(b0));
}
DEVI float rcp(float x) { float y; asm("rcp.approx.ftz.f32 %0, %1;" : "=f"(y) : "f"(x)); return y; }
DEVI uint32_t movm(uint32_t a) { uint32_t d; asm volatile("movmatrix.sync.aligned.m8n8.trans.b16 %0, %1;" : "=r"(d) : "r"(a)); return d; }
DEVI uint4 lds128(uint32_t a) {
    uint4 v;
    asm volatile("ld.shared.v4.u32 {%0,%1,%2,%3}, [%4];" : "=r"(v.x), "=r"(v.y), "=r"(v.z), "=r"(v.w) : "r"(a) : "memory");
    return v;
}
DEVI float bf_lo(uint32_t w) { return __uint_as_float(w << 16); }
DEVI float bf_hi(uint32_t w) { return __uint_as_float(w & 0xFFFF0000u); }
DEVI void tma_load_3d(uint32_t dst, const CUtensorMap* m, int c0, int c1, int c2, uint32_t bar) {
    asm volatile("cp.async.bulk.tensor.3d.shared::cluster.global.mbarrier::complete_tx::bytes [%0], [%1, {%3, %4, %5}], [%2];"
                 ::"r"(dst), "l"(m), "r"(bar), "r"(c0), "r"(c1), "r"(c2) : "memory");
}
DEVI uint32_t lds32(uint32_t a) { uint32_t v; asm volatile("ld.shared.u32 %0, [%1];" : "=r"(v) : "r"(a) : "memory"); return v; }
DEVI uint32_t clk32() { uint32_t c; asm volatile("mov.u32 %0, %%clock;" : "=r"(c)::"memory"); return c; }
template <int N> DEVI uint32_t delay(uint32_t z) {
#pragma unroll
    for (int i = 0; i < N; i++) asm volatile("shfl.sync.bfly.b32 %0, %0, 1, 0x1f, 0xffffffff;" : "+r"(z)::"memory");
    return z;
}
DEVI uint32_t opaque(uint32_t x) { asm volatile("shfl.sync.bfly.b32 %0, %0, 0, 0x1f, 0xffffffff;" : "+r"(x)); return x; }
DEVI void settle_g0(int& budget, uint2 a, uint2 b, uint2 c, const void* pK, const void* pC, const void* pD, uint32_t fb, uint32_t fc, uint32_t mw0, uint32_t mw1) {
    asm volatile("{\n.reg .pred p, q, p<3>;\n.reg .b32 m, n;\nL:\nmax.u32 m, %1, %2;\nsetp.eq.u32 p0, m, 0xFFFFFFFF;\nmax.u32 m, %3, %4;\nsetp.eq.u32 p1, m, 0xFFFFFFFF;\nmax.u32 m, %5, %6;\nsetp.eq.u32 p2, m, 0xFFFFFFFF;\nor.pred p, p0, p1;\nor.pred p, p, p2;\nvote.sync.any.pred p, p, 0xffffffff;\n@!p bra D;\n@p0 ld.relaxed.gpu.global.v2.u32 {%1,%2}, [%7];\n@p1 ld.relaxed.gpu.global.v2.u32 {%3,%4}, [%8];\n@p2 ld.relaxed.gpu.global.v2.u32 {%5,%6}, [%9];\nsub.s32 %0, %0, 1;\nsetp.gt.s32 q, %0, 0;\n@q bra L;\nD:\nadd.rn.bf16x2 m, %12, %1;\nst.shared.u32 [%10], m;\nadd.rn.bf16x2 n, %13, %2;\nst.shared.u32 [%10+128], n;\nadd.rn.bf16x2 m, %3, %5;\nst.shared.u32 [%11], m;\nadd.rn.bf16x2 n, %4, %6;\nst.shared.u32 [%11+128], n;\n}\n" : "+r"(budget), "+r"(a.x), "+r"(a.y), "+r"(b.x), "+r"(b.y), "+r"(c.x), "+r"(c.y) : "l"(pK), "l"(pC), "l"(pD), "r"(fb), "r"(fc), "r"(mw0), "r"(mw1) : "memory");
}

DEVI void poll_g0(int& budget, uint32_t z, const void* pK, const void* pC, const void* pD, uint32_t fb, uint32_t fc, uint32_t mw0, uint32_t mw1) {
    asm volatile("{\n.reg .pred p, q, p<3>;\n.reg .b32 m, n, r<6>;\n.reg .u64 a<3>, zz;\ncvt.u64.u32 zz, %1;\nadd.u64 a0, %2, zz;\nadd.u64 a1, %3, zz;\nadd.u64 a2, %4, zz;\nld.relaxed.gpu.global.v2.u32 {r0,r1}, [a0];\nld.relaxed.gpu.global.v2.u32 {r2,r3}, [a1];\nld.relaxed.gpu.global.v2.u32 {r4,r5}, [a2];\nL:\nmax.u32 m, r0, r1;\nsetp.eq.u32 p0, m, 0xFFFFFFFF;\nmax.u32 m, r2, r3;\nsetp.eq.u32 p1, m, 0xFFFFFFFF;\nmax.u32 m, r4, r5;\nsetp.eq.u32 p2, m, 0xFFFFFFFF;\nmov.pred p, p0;\nor.pred p, p, p1;\nor.pred p, p, p2;\nvote.sync.any.pred p, p, 0xffffffff;\n@!p bra D;\n@p0 ld.relaxed.gpu.global.v2.u32 {r0,r1}, [a0];\n@p1 ld.relaxed.gpu.global.v2.u32 {r2,r3}, [a1];\n@p2 ld.relaxed.gpu.global.v2.u32 {r4,r5}, [a2];\nsub.s32 %0, %0, 1;\nsetp.gt.s32 q, %0, 0;\n@q bra L;\nD:\nadd.rn.bf16x2 m, %7, r0;\nst.shared.u32 [%5], m;\nadd.rn.bf16x2 n, %8, r1;\nst.shared.u32 [%5+128], n;\nadd.rn.bf16x2 m, r2, r4;\nst.shared.u32 [%6], m;\nadd.rn.bf16x2 n, r3, r5;\nst.shared.u32 [%6+128], n;\n}\n" : "+r"(budget) : "r"(z), "l"(pK), "l"(pC), "l"(pD), "r"(fb), "r"(fc), "r"(mw0), "r"(mw1) : "memory");
}

DEVI void poll_g1(float (&f)[8], int& budget, uint32_t z, const void* src) {
    asm volatile("{\n.reg .pred p, q, p<2>;\n.reg .b32 m, n, r<8>;\n.reg .u64 a, zz;\n.reg .f32 x, y;\ncvt.u64.u32 zz, %9;\nadd.u64 a, %10, zz;\nld.relaxed.gpu.global.v4.u32 {r0,r1,r2,r3}, [a+0];\nld.relaxed.gpu.global.v4.u32 {r4,r5,r6,r7}, [a+512];\nL:\nmax.u32 m, r0, r1;\nmax.u32 m, m, r2;\nmax.u32 m, m, r3;\nsetp.eq.u32 p0, m, 0xFFFFFFFF;\nmax.u32 m, r4, r5;\nmax.u32 m, m, r6;\nmax.u32 m, m, r7;\nsetp.eq.u32 p1, m, 0xFFFFFFFF;\nmov.pred p, p0;\nor.pred p, p, p1;\nvote.sync.any.pred p, p, 0xffffffff;\n@!p bra D;\n@p0 ld.relaxed.gpu.global.v4.u32 {r0,r1,r2,r3}, [a+0];\n@p1 ld.relaxed.gpu.global.v4.u32 {r4,r5,r6,r7}, [a+512];\nsub.s32 %8, %8, 1;\nsetp.gt.s32 q, %8, 0;\n@q bra L;\nD:\nshl.b32 m, r0, 16;\nshl.b32 n, r4, 16;\nmov.b32 x, m;\nmov.b32 y, n;\nadd.f32 %0, x, y;\nand.b32 m, r0, 0xFFFF0000;\nand.b32 n, r4, 0xFFFF0000;\nmov.b32 x, m;\nmov.b32 y, n;\nadd.f32 %1, x, y;\nshl.b32 m, r1, 16;\nshl.b32 n, r5, 16;\nmov.b32 x, m;\nmov.b32 y, n;\nadd.f32 %2, x, y;\nand.b32 m, r1, 0xFFFF0000;\nand.b32 n, r5, 0xFFFF0000;\nmov.b32 x, m;\nmov.b32 y, n;\nadd.f32 %3, x, y;\nshl.b32 m, r2, 16;\nshl.b32 n, r6, 16;\nmov.b32 x, m;\nmov.b32 y, n;\nadd.f32 %4, x, y;\nand.b32 m, r2, 0xFFFF0000;\nand.b32 n, r6, 0xFFFF0000;\nmov.b32 x, m;\nmov.b32 y, n;\nadd.f32 %5, x, y;\nshl.b32 m, r3, 16;\nshl.b32 n, r7, 16;\nmov.b32 x, m;\nmov.b32 y, n;\nadd.f32 %6, x, y;\nand.b32 m, r3, 0xFFFF0000;\nand.b32 n, r7, 0xFFFF0000;\nmov.b32 x, m;\nmov.b32 y, n;\nadd.f32 %7, x, y;\n}\n" : "=&f"(f[0]), "=&f"(f[1]), "=&f"(f[2]), "=&f"(f[3]), "=&f"(f[4]), "=&f"(f[5]), "=&f"(f[6]), "=&f"(f[7]), "+r"(budget) : "r"(z), "l"(src) : "memory");
}

DEVI void poll_g2(int& budget, uint32_t z, const void* src, uint32_t dst) {
    asm volatile("{\n.reg .pred p, q, p<4>;\n.reg .b32 m, r<16>;\n.reg .u64 a, zz;\ncvt.u64.u32 zz, %1;\nadd.u64 a, %2, zz;\nld.relaxed.gpu.global.v4.u32 {r0,r1,r2,r3}, [a+0];\nld.relaxed.gpu.global.v4.u32 {r4,r5,r6,r7}, [a+1024];\nld.relaxed.gpu.global.v4.u32 {r8,r9,r10,r11}, [a+2048];\nld.relaxed.gpu.global.v4.u32 {r12,r13,r14,r15}, [a+3072];\nL:\nmax.u32 m, r0, r1;\nmax.u32 m, m, r2;\nmax.u32 m, m, r3;\nsetp.eq.u32 p0, m, 0xFFFFFFFF;\nmax.u32 m, r4, r5;\nmax.u32 m, m, r6;\nmax.u32 m, m, r7;\nsetp.eq.u32 p1, m, 0xFFFFFFFF;\nmax.u32 m, r8, r9;\nmax.u32 m, m, r10;\nmax.u32 m, m, r11;\nsetp.eq.u32 p2, m, 0xFFFFFFFF;\nmax.u32 m, r12, r13;\nmax.u32 m, m, r14;\nmax.u32 m, m, r15;\nsetp.eq.u32 p3, m, 0xFFFFFFFF;\nmov.pred p, p0;\nor.pred p, p, p1;\nor.pred p, p, p2;\nor.pred p, p, p3;\nvote.sync.any.pred p, p, 0xffffffff;\n@!p bra D;\n@p0 ld.relaxed.gpu.global.v4.u32 {r0,r1,r2,r3}, [a+0];\n@p1 ld.relaxed.gpu.global.v4.u32 {r4,r5,r6,r7}, [a+1024];\n@p2 ld.relaxed.gpu.global.v4.u32 {r8,r9,r10,r11}, [a+2048];\n@p3 ld.relaxed.gpu.global.v4.u32 {r12,r13,r14,r15}, [a+3072];\nsub.s32 %0, %0, 1;\nsetp.gt.s32 q, %0, 0;\n@q bra L;\nD:\nst.shared.v4.u32 [%3+0], {r0,r1,r2,r3};\nst.shared.v4.u32 [%3+1024], {r4,r5,r6,r7};\nst.shared.v4.u32 [%3+2048], {r8,r9,r10,r11};\nst.shared.v4.u32 [%3+3072], {r12,r13,r14,r15};\n}\n" : "+r"(budget) : "r"(z), "l"(src), "r"(dst) : "memory");
}

DEVI void bulk_red_bf16(void* dst, uint32_t src, uint32_t bytes) {
    asm volatile("cp.reduce.async.bulk.global.shared::cta.bulk_group.add.noftz.bf16 [%0], [%1], %2;" ::"l"(dst), "r"(src), "r"(bytes) : "memory");
}
DEVI void fence_proxy_async_global() { asm volatile("fence.proxy.async.global;" ::: "memory"); }
DEVI uint32_t ldg_poll1(const void* p) { uint32_t v; asm volatile("ld.relaxed.gpu.global.u32 %0, [%1];" : "=r"(v) : "l"(p) : "memory"); return v; }
#define PROBE_MAX 40
DEVI uint32_t near_page(char* p, uint32_t scratch) {
    uint32_t best0 = ~0u, best1 = ~0u;
#pragma unroll 1
    for (int r = 0; r < PROBE_MAX; r++) {
        if (r >= 8 && min(best0, best1) < 340u && max(best0, best1) - min(best0, best1) > 100u && max(best0, best1) < 600u) break;
        uint32_t t0, t1, v;
        asm volatile("mov.u32 %0, %%clock;\n"
                     "atom.relaxed.gpu.global.exch.b32 %2, [%3], %4;\n"
                     "st.volatile.shared.u32 [%5], %2;\n"
                     "mov.u32 %1, %%clock;\n" : "=&r"(t0), "=r"(t1), "=r"(v) : "l"(p + (r & 1) * 4096), "r"(SENT), "r"(scratch) : "memory");
        if (r & 1) best1 = min(best1, t1 - t0); else best0 = min(best0, t1 - t0);
    }
    return best1 < best0;
}
#define BAR_MEM 1
#define BAR_QK 2
#define BAR_V 3
#define BAR_O 4
#define BAR_H 5
#define BAR_WG 6
#define BAR_SX 9
#define BAR_VGO 10
#define BAR_XGO 11
#define BAR_VLD 13
#define BAR_G 14
#define BAR_XR 15
#define XS_AT 0
#define G1F 1
#define FBO 0
#define G0P 0
#define VW 1
#define XDUP 0
#define VPF 6
#define NPF0 4
#define NPF1 7
struct TrueT { static constexpr bool value = true; };
struct FalseT { static constexpr bool value = false; };
#define PD0 0
#define PD1 12
#define PD2 0
#define LDA 3
#define VGO_AT 15

DEVI void load_scores(uint32_t sxr, float2 (&sv)[5]) {
    float4 u[6];
#pragma unroll
    for (int t = 0; t < 6; t++) u[t] = lds128f(sxr + t * 64);
#pragma unroll
    for (int t = 0; t < 4; t++) { sv[t].x = u[t].x + u[t].z; sv[t].y = u[t].y + u[t].w; }
    sv[4].x = (u[4].x + u[4].z) + (u[5].x + u[5].z); sv[4].y = (u[4].y + u[4].w) + (u[5].y + u[5].w);
}
DEVI void softmax_p(float2 (&sv)[5], int lim, bool mask, uint32_t (&pa)[5]) {
    const float cs = 0.08838834764831845f * 1.4426950408889634f;
    const float masked = -1000000000.0f / 0.08838834764831845f;
    if (mask) {
#pragma unroll
        for (int t = 0; t < 4; t++) {
            if (2 * t > lim) sv[t].x = masked;
            if (2 * t + 1 > lim) sv[t].y = masked;
        }
    }
    float mx = fmaxf(fmaxf(fmaxf(fmaxf(sv[0].x, sv[0].y), fmaxf(sv[1].x, sv[1].y)), fmaxf(fmaxf(sv[2].x, sv[2].y), fmaxf(sv[3].x, sv[3].y))),
                     fmaxf(sv[4].x, sv[4].y));
    mx = fmaxf(mx, __shfl_xor_sync(~0u, mx, 1));
    mx = fmaxf(mx, __shfl_xor_sync(~0u, mx, 2));
    const float nb = -mx * cs;
#pragma unroll
    for (int t = 0; t < 5; t++) pa[t] = pack_bf16(ex2(fmaf(sv[t].x, cs, nb)), ex2(fmaf(sv[t].y, cs, nb)));
}

__global__ void __launch_bounds__(512, 1)
k2_chain(const __grid_constant__ CUtensorMap tmWq, const __grid_constant__ CUtensorMap tmWk,
         const __grid_constant__ CUtensorMap tmWv, const __grid_constant__ CUtensorMap tmWo,
         const __grid_constant__ CUtensorMap tmX, const __grid_constant__ CUtensorMap tmOA,
         const __grid_constant__ CUtensorMap tmWoA, const __grid_constant__ CUtensorMap tmOut,
         const bf16* __restrict__ mem0, char* __restrict__ cb, uint32_t zero, int by_smid) {
    extern __shared__ __align__(1024) unsigned char smem[];
    const uint32_t sb = smem_u32(smem);
    const int tid = threadIdx.x;
    const int wg = __shfl_sync(~0u, tid >> 7, 0);
    const int cta = chain_role(by_smid);
    const int cta0 = cta;
#define ROLE() const int cta = launder(cta0), h = cta >> 2, j = cta & 3, c = j & 1, kh = j >> 1; (void)h; (void)c; (void)kh
    const int h = cta >> 2, j = cta & 3, c = j & 1, kh = j >> 1;
    pdl_launch();
    if (cta >= 128) {
        out_gemm(&tmOA, &tmWoA, &tmOut, 16, 0, cta - 128, 4, sb);
        if (tid == 480 && cta == 128) {
            long long t0 = clock64();
            while (*(volatile int*)&g_done < 128 * 4) { if (clock64() - t0 > WD_LIMIT) asm volatile("trap;"); }
            g_done = 0;
        }
        return;
    }
#define DONE() do { if ((tid_now() & 127) == 0) atomicAdd(&g_done, 1); if (budget <= 0) g_fail = 1; } while (0)
    const uint32_t bar_w = sb + CS_BAR;
    const uint32_t bar_ws = bar_w + 96;
    const uint32_t bar_x = bar_w + 104;
    const uint32_t bar_gx = bar_w + 112;
    const uint32_t bar_wo = bar_w + 144, bar_xp = bar_w + 152;
    if (tid == 0) {
        for (int i = 0; i < 14; i++) mbar_init(bar_w + 8 * i, i == 12 ? 3 : 1);
        mbar_init(bar_gx, 3);
        mbar_init(bar_gx + 8, 3);
        mbar_init(bar_wo, 2);
        mbar_init(bar_xp, 1);
        mbar_init(bar_xp + 8, 1);
        fence_mbar_init();
    }
    __syncthreads();
    int budget = 1 << 17;
    const uint32_t one = 0x3F803F80u;

    if (wg == 3) {
        asm volatile("setmaxnreg.dec.sync.aligned.u32 48;");
#define PMASK PMASK_H
        const int tid = tid_now(), lane = tid & 31, t128 = tid & 127;
        CALIB(0);
        if (t128 == 0) TLMAX(10);
        sts128(sb + CS_FF + t128 * 16, SENT, SENT, SENT, SENT);
        fence_proxy_async();
#pragma unroll
        for (int i = 0; i < 4; i++) {
            const int ch = i * 128 + t128;
            const uint4 v = *(const uint4*)(mem0 + (ch & 7) * 1024 + kh * 512 + (ch >> 3) * 8);
            sts128(sb + CS_MEM + ch * 16, v.x, v.y, v.z, v.w);
        }
        named_bar(BAR_H, 128);
        if (lane == 0 && t128 < 96) {
            const int w = t128 >> 5;
            const uint32_t pg = near_page(cb + (w == 0 ? G1_OFF + BOX(cta, 0, 0) : G2_OFF + BOX(2 * kh + w - 1, 0, 0)), sb + CS_BAR + 192 + w * 4);
            sts32(sb + CS_BAR + 192 + w * 4, pg);
            if (w == 0) {
#pragma unroll 1
                for (int i = 0; i < 2 * NSLOT; i++) bulk_store(cb + G1_OFF + (BOX(cta, i >> 1, pg) + (i & 1) * 2048), sb + CS_FF, 2048);
                bulk_commit();
                bulk_wait0();
                stg_pub1(cb + GT_OFF + cta * 4, pg);
            }
        }
        if (t128 >= 96) {
            if (lane == 0) {
#pragma unroll 1
                for (int i = 0; i < 2 * NSLOT; i++) bulk_store(cb + G0_OFF + ((i >> 1) * G0_SLOT + cta * 3072 + (i & 1) * 1536), sb + CS_FF, 1536);
            }
            __syncwarp();
#pragma unroll 1
            for (int p = 0; p < 2; p++) {
                named_bar(BAR_G, 384 + 32);
                if (lane == 0) {
                    const uint32_t pk = sb + CS_V1 + p * 12288;
                    char* dst = cb + GX_OFF + (p * GX_SLOT + h * 24576 + c * 4096);
#pragma unroll 1
                    for (int m = 0; m < 3; m++) bulk_store(dst + m * 8192 + kh * 2048, pk + m * 4096 + kh * 2048, 2048);
                    bulk_commit();
                    bulk_wait0();
                    char* f = cb + GF_OFF + (p * 128 + (cta & ~3)) * 16;
                    stg_pub1(f + j * 16, 1u);
                    for (int it = 0; it < (1 << 17) && (ldg_poll1(f + (j ^ 1) * 16) | ldg_poll1(f + (j ^ 2) * 16) | ldg_poll1(f + (j ^ 3) * 16)) != 1u; it++) {}
                    fence_proxy_async_global();
                    if (p) {
                        const char* src = cb + GX_OFF + h * 24576;
                        mbar_expect_tx(bar_gx, 2048); mbar_expect_tx(bar_gx, 8192); mbar_expect_tx(bar_gx, 8192);
                        bulk_load(sb + CS_QX, src + j * 1024, 1024, bar_gx);
                        bulk_load(sb + CS_QX + 1024, src + 4096 + j * 1024, 1024, bar_gx);
                        bulk_load(sb + CS_KX, src + 8192, 8192, bar_gx);
                        bulk_load(sb + CS_V0, src + 16384, 8192, bar_gx);
                    }
#pragma unroll 1
                    for (int m = 0; m < 3; m++) bulk_red_bf16(dst + m * 8192 + (kh ^ 1) * 2048, pk + m * 4096 + (kh ^ 1) * 2048, 2048);
                    bulk_commit();
                }
                __syncwarp();
            }
            bulk_wait0();
        }
        named_bar(BAR_H, 128);
        uint32_t ka[16];
        auto load_keys = [&](int t) {
            const int ln = tid_now() & 31, w4 = (tid_now() & 127) >> 5, r8 = ln & 7, mt = w4 & 1;
            const uint32_t ka0 = sb + CS_KX + (w4 * 4 + (ln >> 4)) * 512 + r8 * 64 + (((2 * mt + ((ln >> 3) & 1)) ^ (r8 >> 1)) << 4);
            const uint32_t ka1 = ka0 + (mt ? -2048 : 2048);
            mbar_wait(bar_gx + (t & 1) * 8, (t >> 1) & 1);
            ldsm4t(ka[0], ka[1], ka[2], ka[3], ka0);
            ldsm4t(ka[4], ka[5], ka[6], ka[7], ka0 + 1024);
            ldsm4t(ka[8], ka[9], ka[10], ka[11], ka1);
            ldsm4t(ka[12], ka[13], ka[14], ka[15], ka1 + 1024);
        };
        for (int s = 0; s < NSEG; s++) {
            ROLE();
            PROF(0);
            named_bar(BAR_MEM, 512);
            if (s == 0) load_keys(0);
            const int ln = (tid_now() & 31), w4 = (tid_now() & 127) >> 5, g = ln >> 2, q = ln & 3, r8 = ln & 7, mt = w4 & 1;
            const uint32_t kma = sb + CS_KF + (4 * w4 + ((ln >> 3) & 1) * 2 + (ln >> 4)) * 128 + r8 * 16;
            const uint32_t va0 = sb + CS_VX(s) + (4 * w4 + ((ln >> 3) & 1)) * 512 + r8 * 64 + (((ln >> 4) ^ (r8 >> 1)) << 4);
            const uint32_t lw = sb + ln * 16 + w4 * 512;
            const uint32_t sxw = sb + CS_SX + (2 * q) * 448 + (q & 1) * 64 + (g >> 1) * 16 + (g & 1) * 4;
            const uint32_t sxx = sxw + (2 * mt) * 64 + (w4 >> 1) * 8;
            const uint32_t sxm = sxw + (4 + (w4 >> 1)) * 64 + mt * 8;
            const uint32_t sxr = sb + CS_SX + g * 448 + ((g >> 1) & 1) * 64 + q * 16;
            PROF(1);
            uint32_t qx[4];
            {
                uint32_t b0, b1, b2, b3;
                float u[4] = {0.f, 0.f, 0.f, 0.f}, v[4] = {0.f, 0.f, 0.f, 0.f};
                ldsm4t(qx[0], qx[1], qx[2], qx[3], lw + CS_QX);
                ldsm4t(b0, b1, b2, b3, (lw ^ 512) + CS_QX);
                mma16816(u, ka[0], ka[1], ka[2], ka[3], qx[0], qx[1]);
                mma16816(v, ka[4], ka[5], ka[6], ka[7], qx[2], qx[3]);
                mma16816(u, ka[8], ka[9], ka[10], ka[11], b0, b1);
                mma16816(v, ka[12], ka[13], ka[14], ka[15], b2, b3);
                sts32(sxx + 3584, __float_as_uint(u[0] + v[0])); sts32(sxx + 3584 + 448, __float_as_uint(u[1] + v[1]));
                sts32(sxx + 3584 + 64, __float_as_uint(u[2] + v[2])); sts32(sxx + 3584 + 448 + 64, __float_as_uint(u[3] + v[3]));
            }
            PROF(2);
            named_bar(BAR_QK, 384);
            uint32_t va[16];
            {
                uint32_t m0, m1, m2, m3, b0, b1, b2, b3, e0, e1, e2, e3;
                ldsm4t(b0, b1, b2, b3, lw + CS_QF);
                ldsm4t(e0, e1, e2, e3, (lw ^ 512) + CS_QF);
                ldsm4t(m0, m1, m2, m3, kma);
                PROF(3);
                float u0[4] = {0.f, 0.f, 0.f, 0.f}, u1[4] = {0.f, 0.f, 0.f, 0.f}, v0[4] = {0.f, 0.f, 0.f, 0.f}, v1[4] = {0.f, 0.f, 0.f, 0.f};
                float y0[4] = {0.f, 0.f, 0.f, 0.f}, y1[4] = {0.f, 0.f, 0.f, 0.f};
                mma16816(u0, ka[0], ka[1], ka[2], ka[3], b0, b1);
                mma16816(u1, ka[4], ka[5], ka[6], ka[7], b2, b3);
                mma16816(v0, m0, m1, m2, m3, b0, b1);
                mma16816(v1, m0, m1, m2, m3, b2, b3);
                mma16816(u0, ka[8], ka[9], ka[10], ka[11], e0, e1);
                mma16816(u1, ka[12], ka[13], ka[14], ka[15], e2, e3);
                mma16816(y0, m0, m1, m2, m3, qx[0], qx[1]);
                mma16816(y1, m0, m1, m2, m3, qx[2], qx[3]);
                sts32(sxm, __float_as_uint(v0[0] + v1[2])); sts32(sxm + 448, __float_as_uint(v0[1] + v1[3]));
                sts32(sxx, __float_as_uint(u0[0] + u1[0])); sts32(sxx + 448, __float_as_uint(u0[1] + u1[1]));
                sts32(sxx + 64, __float_as_uint(u0[2] + u1[2])); sts32(sxx + 448 + 64, __float_as_uint(u0[3] + u1[3]));
                sts32(sxm + 3584, __float_as_uint(y0[0] + y1[2])); sts32(sxm + 3584 + 448, __float_as_uint(y0[1] + y1[3]));
                ldsm4(va[0], va[1], va[2], va[3], va0);
                ldsm4(va[4], va[5], va[6], va[7], va0 ^ 32);
                ldsm4(va[8], va[9], va[10], va[11], va0 + 1024);
                ldsm4(va[12], va[13], va[14], va[15], (va0 ^ 32) + 1024);
            }
            PROF(4);
            named_bar(BAR_H, 128);
            {
                uint32_t pa[5], vm[4];
                float2 sv[5];
                load_scores(sxr, sv);
                if (NPF1 > NPF0) bar_arrive(BAR_G, 384);
                asm volatile("{\n.reg .pred q;\nbar.arrive %2, 256;\nsetp.eq.u32 q, %0, %1;\n@q bra.uni S;\ntrap;\nS:\n}\n"
                             ::"r"(__float_as_uint(sv[4].x) & zero), "r"(zero), "n"(BAR_SX) : "memory");
                softmax_p(sv, 0, false, pa);
                float o0[4] = {0.f, 0.f, 0.f, 0.f}, o1[4] = {0.f, 0.f, 0.f, 0.f}, ls[4] = {0.f, 0.f, 0.f, 0.f};
                mma16816(ls, one, one, one, one, pa[0], pa[1]);
                mma16816(o0, va[0], va[1], va[2], va[3], pa[0], pa[1]);
                mma16816(o1, va[8], va[9], va[10], va[11], pa[0], pa[1]);
                mma16816(ls, one, one, one, one, pa[2], pa[3]);
                mma16816(o0, va[4], va[5], va[6], va[7], pa[2], pa[3]);
                mma16816(o1, va[12], va[13], va[14], va[15], pa[2], pa[3]);
                mma1688(ls, one, one, pa[4]);
                PROF(5);
                named_bar(BAR_V, 256);
                ldsm4(vm[0], vm[1], vm[2], vm[3], lw + CS_VF);
                PROF(6);
                mma1688(o0, vm[0], vm[1], pa[4]);
                mma1688(o1, vm[2], vm[3], pa[4]);
                const float i0 = rcp(ls[0]), i1 = rcp(ls[1]);
                stsm4(lw + CS_OM, pack_bf16(o0[0] * i0, o0[1] * i1), pack_bf16(o0[2] * i0, o0[3] * i1),
                      pack_bf16(o1[0] * i0, o1[1] * i1), pack_bf16(o1[2] * i0, o1[3] * i1));
            }
            if (s + 1 < NSEG) bar_arrive(BAR_O, 384);
            if (s + 1 == NSEG) break;
            PROF(7);
            {
                const int lt = (tid_now() & 127);
                const uint32_t pg1 = lds32(sb + CS_BAR + 192) * 4096;
                const uint32_t pg2 = lds32(sb + CS_BAR + 196 + (lt >> 6) * 4) * 4096;
                const char* src = cb + G1_OFF + (BOX(cta, s & (NSLOT - 1), 0) + pg1 + (lt >> 5) * 1024 + (lt & 31) * 16);
                char* g2p = cb + G2_OFF + (BOX(cta >> 5, s & (NSLOT - 1), 0) + (cta & 31) * 128 + (lt & 31) * 4);
                const uint32_t ra = sb + CS_RED + (lt >> 5) * 256 + ((lt >> 3) & 3) * 64 + (lt & 7) * 4;
                float f[8];
                poll_g1(f, budget, delay<PD1>(lds32(sb + CS_OM + lt * 4) & zero), src);
                PROF(9);
                const bool b4 = lt & 16, b3 = lt & 8;
                float r[4];
#pragma unroll
                for (int i = 0; i < 4; i++) {
                    const float send = b4 ? f[i] : f[i + 4], keep = b4 ? f[i + 4] : f[i];
                    r[i] = keep + __shfl_xor_sync(~0u, send, 16);
                }
                float z[2];
#pragma unroll
                for (int i = 0; i < 2; i++) {
                    const float send = b3 ? r[i] : r[i + 2], keep = b3 ? r[i + 2] : r[i];
                    z[i] = keep + __shfl_xor_sync(~0u, send, 8);
                }
                sts32(ra, __float_as_uint(z[0]));
                sts32(ra + 32, __float_as_uint(z[1]));
                PROF(10);
                named_bar(BAR_H, 128);
                if (lt < 32) {
                    const float2 p0 = lds64f(sb + CS_RED + lt * 8), p1 = lds64f(sb + CS_RED + 256 + lt * 8);
                    const float2 p2 = lds64f(sb + CS_RED + 512 + lt * 8), p3 = lds64f(sb + CS_RED + 768 + lt * 8);
                    const uint32_t mw = pack_bf16((p0.x + p1.x) + (p2.x + p3.x), (p0.y + p1.y) + (p2.y + p3.y));
                    stg_pub1(g2p, mw);
                    stg_pub1(g2p + 4096, mw);
                } else if (lt < 64) {
                    char* rp = g2p + (((s + 2) & (NSLOT - 1)) - (s & (NSLOT - 1))) * 16384;
                    stg_pub1(rp, SENT);
                    stg_pub1(rp + 4096, SENT);
                }
                PROF(11);
                load_keys(s + 1);
                poll_g2(budget, delay<PD2>(lds32(sb + CS_RED + lt * 4) & zero), cb + G2_OFF + (BOX(2 * kh + (lt >> 6), s & (NSLOT - 1), 0) + pg2 + (lt & 63) * 16), sb + CS_MEM + (lt >> 6) * 4096 + (lt & 63) * 16);
                PROF(12);
            }
        }
        if (t128 == 0) TLMAX(5);
        pdl_wait();
        CALIB(1);
        PROF_DUMP();
        DONE();
    } else {
#undef PMASK
#define PMASK PMASK_C
        auto compute = [&](auto role) {
        constexpr bool ISV = decltype(role)::value;
        const int tid = tid_now(), lane = tid & 31, t128 = tid & 127;
        constexpr int NRK = ISV ? NRK_V : NRK_QK, NST = ISV ? 4 : 3;
        const int w4 = (tid >> 5) & 3;
        const uint32_t l16 = sb + lane * 16;
        const CUtensorMap* tmW = ISV ? &tmWv : (wg == 0 ? &tmWq : &tmWk);
        const int wcol = h * 128 + c * 64;
        const uint32_t stg = sb + CS_STG + wg * 24576;
        const uint32_t wsb = sb + CS_WS + wg * (32 - NRK_QK) * 2048;
        if (t128 == 0) {
#pragma unroll 1
            for (int i = 0; i < NST; i++) {
                mbar_expect_tx(bar_w + 8 * (wg * 4 + i), 8192);
                tma_load_2d(stg + i * 8192, tmW, wcol, kh * 512 + i * 64, bar_w + 8 * (wg * 4 + i));
            }
            mbar_expect_tx(bar_ws, (32 - NRK) * 2048);
#pragma unroll 1
            for (int i = NRK / 4; i < 8; i++) tma_load_2d(wsb + (i - NRK / 4) * 8192, tmW, wcol, kh * 512 + i * 64, bar_ws);
            if (!ISV) {
                mbar_expect_tx(bar_xp + 8 * wg, 32768);
                tma_load_3d(sb + CS_WO + wg * 32768, &tmX, 0, wg * 32, kh * 8, bar_xp + 8 * wg);
            }
        }
        __syncwarp();
        const uint32_t arow = (lane & 7) + (lane >> 4) * 8;
        const uint32_t aoff = arow * 128 + (((2 * w4 + ((lane >> 3) & 1)) ^ (lane & 7)) << 4);
        uint32_t wr[NRK * 4];
#pragma unroll
        for (int i = 0; i < NRK / 4; i++) {
            mbar_wait(bar_w + 8 * (wg * 4 + (i % NST)), (i / NST) & 1);
#pragma unroll
            for (int k = 0; k < 4; k++)
                ldsm4t(wr[(i * 4 + k) * 4], wr[(i * 4 + k) * 4 + 1], wr[(i * 4 + k) * 4 + 2], wr[(i * 4 + k) * 4 + 3],
                       stg + (i % NST) * 8192 + k * 2048 + aoff);
            if (i + NST < NRK / 4) {
                named_bar(BAR_WG + wg, 128);
                if (t128 == 0) {
                    mbar_expect_tx(bar_w + 8 * (wg * 4 + (i % NST)), 8192);
                    tma_load_2d(stg + (i % NST) * 8192, tmW, wcol, kh * 512 + (i + NST) * 64, bar_w + 8 * (wg * 4 + (i % NST)));
                }
            }
        }
        if (t128 == 0) TLMAX(16);
        named_bar(BAR_XGO, 384);
        if (tid == 160) {
            mbar_expect_tx(bar_x, 32768);
            tma_load_3d(sb + CS_XS, &tmX, 0, 64, kh * 8, bar_x);
        }
        __syncwarp();
        mbar_wait(bar_ws, 0);
        if (t128 == 0) TLMAX(17);
        const uint32_t off0 = G0P ? 0u : opaque(G0_OFF + cta * 3072 + (wg * 128 + t128) * 8);
        const uint32_t off1 = opaque(G1_OFF + BOX(32 * j + 4 * (4 * wg + w4), 0, 0) + h * 128 + lane * 4);
        uint32_t pgw = 0;
        auto add_parked = [&](int s) {
            ROLE();
            if ((tid_now() & 127) == 0 && s + 2 < NSEG) {
                fence_proxy_async_global();
                bulk_red_bf16(cb + GX_OFF + (((s + 2) & (NSLOT - 1)) * GX_SLOT + h * 24576 + wg * 8192 + c * 4096 + (kh ^ 1) * 2048),
                              sb + CS_XP + wg * 4096 + (kh ^ 1) * 2048, 2048);
                bulk_commit();
            }
            __syncwarp();
        };
        auto fetch_next = [&](int s) {
            ROLE();
            const int tn = tid_now(), w4 = (tn >> 5) & 3;
            if ((tn & 31) == 0 && s + 1 < NSEG) {
                if (w4 == 0) {
                    const int rs = (s + 2) & (NSLOT - 1);
                    char* r1 = cb + G1_OFF + (BOX(cta, rs, 0) + lds32(sb + CS_BAR + 192) * 4096);
                    char* r0 = cb + G0_OFF + (rs * G0_SLOT + cta * 3072);
                    bulk_store(r1, sb + CS_FF, 2048); bulk_store(r1 + 2048, sb + CS_FF, 2048);
                    bulk_store(r0, sb + CS_FF, 2048); bulk_store(r0 + 2048, sb + CS_FF, 1024);
                    bulk_commit();
                } else {
                    fence_proxy_async_global();
                    const char* src = cb + GX_OFF + (((s + 1) & (NSLOT - 1)) * GX_SLOT + h * 24576);
                    const uint32_t br = bar_gx + ((s + 1) & 1) * 8;
                    if (w4 == 3) {
                        mbar_expect_tx(br, 2048);
                        bulk_load(sb + CS_QX, src + j * 1024, 1024, br);
                        bulk_load(sb + CS_QX + 1024, src + 4096 + j * 1024, 1024, br);
                    } else {
                        mbar_expect_tx(br, 8192);
                        bulk_load(sb + (w4 == 2 ? CS_VX(s + 1) : CS_KX), src + w4 * 8192, 8192, br);
                    }
                }
            }
            __syncwarp();
        };
        uint32_t pa[5];
        auto xrows_p = [&]() {
            ROLE();
            const int ln = tid_now() & 31, g = ln >> 2, q = ln & 3;
            float2 sv[5];
            load_scores(sb + CS_SX + 3584 + g * 448 + ((g >> 1) & 1) * 64 + q * 16, sv);
            softmax_p(sv, 8 * j + g - 8 * q, true, pa);
        };
        auto xrows_o = [&](int s) {
            ROLE();
            const int tn = tid_now(), ln = tn & 31, w4 = (tn >> 5) & 3, r8 = ln & 7;
            const uint32_t va0 = sb + CS_VX(s) + (4 * w4 + ((ln >> 3) & 1)) * 512 + r8 * 64 + (((ln >> 4) ^ (r8 >> 1)) << 4);
            uint32_t va[16], vm[4];
            ldsm4(va[0], va[1], va[2], va[3], va0);
            ldsm4(va[4], va[5], va[6], va[7], va0 ^ 32);
            ldsm4(va[8], va[9], va[10], va[11], va0 + 1024);
            ldsm4(va[12], va[13], va[14], va[15], (va0 ^ 32) + 1024);
            ldsm4(vm[0], vm[1], vm[2], vm[3], sb + ln * 16 + w4 * 512 + CS_VF);
            float o0[4] = {0.f, 0.f, 0.f, 0.f}, o1[4] = {0.f, 0.f, 0.f, 0.f}, ls[4] = {0.f, 0.f, 0.f, 0.f};
            mma16816(ls, one, one, one, one, pa[0], pa[1]);
            mma16816(o0, va[0], va[1], va[2], va[3], pa[0], pa[1]);
            mma16816(o1, va[8], va[9], va[10], va[11], pa[0], pa[1]);
            mma16816(ls, one, one, one, one, pa[2], pa[3]);
            mma16816(o0, va[4], va[5], va[6], va[7], pa[2], pa[3]);
            mma16816(o1, va[12], va[13], va[14], va[15], pa[2], pa[3]);
            mma1688(ls, one, one, pa[4]);
            mma1688(o0, vm[0], vm[1], pa[4]);
            mma1688(o1, vm[2], vm[3], pa[4]);
            const float i0 = rcp(ls[0]), i1 = rcp(ls[1]);
            uint32_t* og = (uint32_t*)(g_oB + (size_t)(s * 32 + 8 * j + (ln >> 2)) * 4096 + h * 128 + w4 * 32) + (ln & 3);
            og[0] = movm(pack_bf16(o0[0] * i0, o0[1] * i1)); og[4] = movm(pack_bf16(o0[2] * i0, o0[3] * i1));
            og[8] = movm(pack_bf16(o1[0] * i0, o1[1] * i1)); og[12] = movm(pack_bf16(o1[2] * i0, o1[3] * i1));
        };
#pragma unroll
        for (int i = 0; i < 5; i++) pa[i] = 0;
        uint32_t tl[(32 - NRK) * 4];
        if (!ISV && !CFG) {
#pragma unroll
            for (int k = 0; k < 32 - NRK; k++) ldsm4t(tl[4 * k], tl[4 * k + 1], tl[4 * k + 2], tl[4 * k + 3], wsb + k * 2048 + aoff);
        }
        for (int s = -3; s < NSEG; s++) {
            ROLE();
            if (s >= 0) {
                const int sl = s & (NSLOT - 1);
#pragma unroll
                for (int k = 0; k < (ISV ? VPF : (CFG ? 32 - NRK : 0)); k++) ldsm4t(tl[4 * k], tl[4 * k + 1], tl[4 * k + 2], tl[4 * k + 3], wsb + k * 2048 + aoff);
                char* g0p = cb + (G0P ? opaque(G0_OFF + sl * G0_SLOT + cta * 3072 + tid_now() * 8) : off0 + sl * G0_SLOT);
                PROF(0);
                float ac[4][4];
#pragma unroll
                for (int i = 0; i < 4; i++) ac[i][0] = ac[i][1] = ac[i][2] = ac[i][3] = 0.f;
                if (!ISV) named_bar(BAR_MEM, 512);
                if (ISV) {
                    if (VW && w4 == 0) bulk_wait0();
                    named_bar(BAR_VGO, 384);
                }
                PROF(1);
                {
                    uint32_t bq[16][4];
#pragma unroll
                    for (int pp = 0; pp < 16 + LDA; pp++) {
                        if (pp < 16) {
                            const int p = (pp + NRK / 2) & 15;
                            if (pp == VGO_AT && !ISV) bar_arrive(BAR_VGO, 384);
                            if (pp == 15 && ISV) bar_arrive(BAR_VLD, 384);
                            ldsm4(bq[pp][0], bq[pp][1], bq[pp][2], bq[pp][3], l16 + CS_MEM + p * 512);
                            if (ISV && 2 * pp >= VPF && 2 * pp < 32 - NRK) {
                                ldsm4t(tl[8 * pp], tl[8 * pp + 1], tl[8 * pp + 2], tl[8 * pp + 3], wsb + (2 * pp) * 2048 + aoff);
                                ldsm4t(tl[8 * pp + 4], tl[8 * pp + 5], tl[8 * pp + 6], tl[8 * pp + 7], wsb + (2 * pp + 1) * 2048 + aoff);
                            }
                        }
                        if (pp >= LDA) {
                            const int u = pp - LDA, p = (u + NRK / 2) & 15;
                            if (2 * p + 1 < NRK) {
                                mma16816(ac[(u & 1) * 2], wr[8 * p], wr[8 * p + 1], wr[8 * p + 2], wr[8 * p + 3], bq[u][0], bq[u][1]);
                                mma16816(ac[(u & 1) * 2 + 1], wr[8 * p + 4], wr[8 * p + 5], wr[8 * p + 6], wr[8 * p + 7], bq[u][2], bq[u][3]);
                            } else {
                                const int t = (2 * p - NRK) * 4;
                                mma16816(ac[(u & 1) * 2], tl[t], tl[t + 1], tl[t + 2], tl[t + 3], bq[u][0], bq[u][1]);
                                mma16816(ac[(u & 1) * 2 + 1], tl[t + 4], tl[t + 5], tl[t + 6], tl[t + 7], bq[u][2], bq[u][3]);
                            }
                        }
                    }
                }
                const uint32_t mw0 = pack_bf16((ac[0][0] + ac[1][0]) + (ac[2][0] + ac[3][0]), (ac[0][1] + ac[1][1]) + (ac[2][1] + ac[3][1]));
                const uint32_t mw1 = pack_bf16((ac[0][2] + ac[1][2]) + (ac[2][2] + ac[3][2]), (ac[0][3] + ac[1][3]) + (ac[2][3] + ac[3][3]));
                if (!ISV || !VW) asm volatile("{\n.reg .pred p;\nsetp.eq.u32 p, %0, 0;\n@p cp.async.bulk.wait_group 0;\n}\n" ::"r"((__float_as_uint(ac[0][0]) & zero) | w4) : "memory");
                stg_pub2(g0p, mw0, mw1);
                PROF(2);
#define XS_LOAD(t) do { if (tid_now() == (t) && s + 3 < NSEG) { mbar_expect_tx(bar_x, 32768); \
                    tma_load_3d(sb + CS_XS, &tmX, 0, (s + 3) * 32, kh * 8, bar_x); } __syncwarp(); } while (0)
#define GATHER() do { \
                    const int tg = tid_now(); const uint32_t fb0 = sb + CS_QF + wg * 2048 + ((tg >> 5) & 3) * 256 + (tg & 31) * 4, fb = FBO ? opaque(fb0) : fb0; \
                    poll_g0(budget, delay<PD0>(mw0 & zero), g0p + ((j ^ 2) - j) * 3072, g0p + ((j ^ 1) - j) * 3072, g0p + ((j ^ 3) - j) * 3072, \
                            fb + c * 1024, fb + (c ^ 1) * 1024, mw0, mw1); } while (0)
                if (!ISV) {
                    const int wi = 4 * wg + w4;
                    const uint32_t wo = sb + CS_WO + (wi >> 1) * 16384 + arow * 128;
                    const uint32_t ch0 = ((4 * (wi & 1) + ((lane >> 3) & 1)) ^ (lane & 7)) << 4;
                    uint32_t pf[64];
#define WO_LD(k) do { ldsm4t(pf[8 * (k)], pf[8 * (k) + 1], pf[8 * (k) + 2], pf[8 * (k) + 3], wo + (k) * 2048 + ch0); \
                      ldsm4t(pf[8 * (k) + 4], pf[8 * (k) + 5], pf[8 * (k) + 6], pf[8 * (k) + 7], wo + (k) * 2048 + (ch0 ^ 32)); } while (0)
                    if (XS_AT == 0) XS_LOAD(160);
                    {
                        const uint32_t fb = sb + CS_QF + wg * 2048 + (2 * w4) * 128 + lane * 4;
                        const char* pK = g0p + ((j ^ 2) - j) * 3072; const char* pC = g0p + ((j ^ 1) - j) * 3072; const char* pD = g0p + ((j ^ 3) - j) * 3072;
                        if (s == 0) mbar_wait(bar_wo, 0);
                        named_bar(BAR_VLD, 384);
                        const uint2 ua = ldg_poll2(pK), ub = ldg_poll2(pC), uc = ldg_poll2(pD);
#pragma unroll
                        for (int k = 0; k < NPF0; k++) WO_LD(k);
                        if (XS_AT == 1) XS_LOAD(160);
                        sched_fence(zero);
                        settle_g0(budget, ua, ub, uc, pK, pC, pD, fb + c * 1024, fb + (c ^ 1) * 1024, mw0, mw1);
                    }
                    bar_arrive(BAR_QK, 384);
                    if (XS_AT == 2) XS_LOAD(160);
                    PROF(4);
                    add_parked(s);
                    if (NPF1 > NPF0) named_bar(BAR_G, 384);
                    if (s + 1 == NSEG) break;
#pragma unroll
                    for (int k = NPF0; k < NPF1; k++) WO_LD(k);
                    char* d = cb + (off1 + sl * 16384);
                    char* d0 = d + (pgw & 1) * 4096;
                    char* d1 = d + (8192 + (pgw & 2) * 2048);
                    char* d2 = d + (65536 + (pgw & 4) * 1024);
                    char* d3 = d + (65536 + 8192 + (pgw & 8) * 512);
                    PROF(5);
                    named_bar(BAR_O, 384);
                    float oc[4][4];
#pragma unroll
                    for (int i = 0; i < 4; i++) oc[i][0] = oc[i][1] = oc[i][2] = oc[i][3] = 0.f;
                    uint32_t bo[16];
                    ldsm4t(bo[0], bo[1], bo[2], bo[3], l16 + CS_OM);
                    ldsm4t(bo[4], bo[5], bo[6], bo[7], l16 + CS_OM + 512);
                    PROF(6);
#pragma unroll
                    for (int k = 0; k < 8; k++) {
                        mma16816(oc[(k & 1) * 2], pf[8 * k], pf[8 * k + 1], pf[8 * k + 2], pf[8 * k + 3], bo[2 * k], bo[2 * k + 1]);
                        mma16816(oc[(k & 1) * 2 + 1], pf[8 * k + 4], pf[8 * k + 5], pf[8 * k + 6], pf[8 * k + 7], bo[2 * k], bo[2 * k + 1]);
                        if (k < 2) ldsm4t(bo[8 + 4 * k], bo[9 + 4 * k], bo[10 + 4 * k], bo[11 + 4 * k], l16 + CS_OM + (2 + k) * 512);
                        if (NPF1 + k < 8) WO_LD(NPF1 + k);
                    }
                    stg_pub1(d0, pack_bf16(oc[0][0] + oc[2][0], oc[0][1] + oc[2][1]));
                    stg_pub1(d1, pack_bf16(oc[0][2] + oc[2][2], oc[0][3] + oc[2][3]));
                    stg_pub1(d2, pack_bf16(oc[1][0] + oc[3][0], oc[1][1] + oc[3][1]));
                    stg_pub1(d3, pack_bf16(oc[1][2] + oc[3][2], oc[1][3] + oc[3][3]));
                    if (G1F) sched_fence(zero);
#pragma unroll
                    for (int k = 0; k < (CFG ? 0 : 32 - NRK); k++) ldsm4t(tl[4 * k], tl[4 * k + 1], tl[4 * k + 2], tl[4 * k + 3], wsb + k * 2048 + aoff);
                } else {
                    GATHER();
                    bar_arrive(BAR_V, 256);
                    if (XS_AT == 3) XS_LOAD(288);
                    PROF(4);
                    add_parked(s);
                    named_bar(BAR_SX, 256);
                    fetch_next(s);
                    if (s + 1 == NSEG) { xrows_p(); xrows_o(s); }
                    if (s + 1 == NSEG) break;
                }
                PROF(7);
                if (ISV) { xrows_p(); sched_fence(zero); named_bar(0, 384); }
                else { bar_arrive(0, 384); named_bar(BAR_XGO, 256); }
            }
            if (s + 3 < NSEG) {
                if (s < -1) mbar_wait(bar_xp + 8 * (s + 3), 0); else mbar_wait(bar_x, (s + 1) & 1);
                const uint32_t xq = (sb + (s < -1 ? CS_WO + (s + 3) * 32768 : CS_XS)) >> 4;
                float acc[16];
                if (XDUP && s >= -1) {
                wg_fence();
#pragma unroll
                for (int k = 0; k < 32; k++) {
                    const uint64_t bd = desc_q(sb >> 4, CS_XS + (k >> 2) * 4096 + (k & 3) * 32, 16, 1024, 1);
                    if (k < NRK) wgmma_rs_n32(acc, wr[4 * k], wr[4 * k + 1], wr[4 * k + 2], wr[4 * k + 3], bd, k != 0);
                    else if (!ISV && !CFG) wgmma_rs_n32(acc, tl[4 * (k - NRK)], tl[4 * (k - NRK) + 1], tl[4 * (k - NRK) + 2], tl[4 * (k - NRK) + 3], bd, k != 0);
                    else wgmma_ss_n32_ta(acc, desc_q(wsb >> 4, (k - NRK) * 2048, 1024, 1024, 1), bd, k != 0);
                }
                wg_commit();
                wg_wait<0>();
                } else {
                wg_fence();
#pragma unroll
                for (int k = 0; k < 32; k++) {
                    const uint64_t bd = desc_q(xq, (k >> 2) * 4096 + (k & 3) * 32, 16, 1024, 1);
                    if (k < NRK) wgmma_rs_n32(acc, wr[4 * k], wr[4 * k + 1], wr[4 * k + 2], wr[4 * k + 3], bd, k != 0);
                    else if (!ISV && !CFG) wgmma_rs_n32(acc, tl[4 * (k - NRK)], tl[4 * (k - NRK) + 1], tl[4 * (k - NRK) + 2], tl[4 * (k - NRK) + 3], bd, k != 0);
                    else wgmma_ss_n32_ta(acc, desc_q(wsb >> 4, (k - NRK) * 2048, 1024, 1024, 1), bd, k != 0);
                }
                wg_commit();
                wg_wait<0>();
                }
                wg_wait<0>();
                fence_regs(acc);
                if (ISV && s >= -1) bar_arrive(BAR_MEM, 512);
                asm volatile("{\n.reg .pred p;\nsetp.eq.u32 p, %0, 0;\n@p cp.async.bulk.wait_group.read 0;\n}\n" ::"r"(__float_as_uint(acc[0]) & zero) : "memory");
                named_bar(BAR_WG + wg, 128);
                if (s < -1) {
                    named_bar(BAR_XR, 384);
                    if (tid == 160) {
                        mbar_expect_tx(bar_wo, 32768);
#pragma unroll 1
                        for (int i = (s + 3) * 4; i < (s + 3) * 4 + 4; i++)
                            tma_load_2d(sb + CS_WO + i * 8192, &tmWo, j * 256 + (i >> 1) * 64, h * 128 + (i & 1) * 64, bar_wo);
                    }
                    __syncwarp();
                }
                PROF(8);
                const int lt = (tid_now() & 127);
                const uint32_t xp = sb + (s < -1 ? CS_V1 + (s + 3) * 12288 : CS_XP) + wg * 4096;
                if (wg == 0) {
#pragma unroll
                    for (int t = 0; t < 4; t++) {
                        sts32(xp + t * 1024 + (lt >> 5) * 256 + (lt & 31) * 4, pack_bf16(acc[4 * t], acc[4 * t + 1]));
                        sts32(xp + t * 1024 + (lt >> 5) * 256 + (lt & 31) * 4 + 128, pack_bf16(acc[4 * t + 2], acc[4 * t + 3]));
                    }
                } else {
                    const uint32_t xb = xp + (lt >> 5) * 1024 + ((lt >> 2) & 7) * 64 + (((lt ^ (lt >> 3)) & 3) << 4);
                    sts128(xb, pack_bf16(acc[0], acc[1]), pack_bf16(acc[4], acc[5]), pack_bf16(acc[8], acc[9]), pack_bf16(acc[12], acc[13]));
                    sts128(xb + 512, pack_bf16(acc[2], acc[3]), pack_bf16(acc[6], acc[7]), pack_bf16(acc[10], acc[11]), pack_bf16(acc[14], acc[15]));
                }
                fence_proxy_async();
                if (s < -1) bar_arrive(BAR_G, 384 + 32);
                else named_bar(BAR_WG + wg, 128);
                if (lt == 0 && s >= -1) {
                    bulk_store(cb + GX_OFF + (((s + 3) & (NSLOT - 1)) * GX_SLOT + h * 24576 + wg * 8192 + c * 4096 + kh * 2048), xp + kh * 2048, 2048);
                    bulk_commit();
                }
                if (s == -1 && !ISV) {
                    uint4 t;
                    int it = 0;
                    do { t = ldg_poll4(cb + GT_OFF + (32 * j + 4 * (4 * wg + w4)) * 4); } while ((t.x | t.y | t.z | t.w) > 1u && ++it < (1 << 17));
                    pgw = (t.x & 1) | ((t.y & 1) << 1) | ((t.z & 1) << 2) | ((t.w & 1) << 3);
                }
                __syncwarp();
                PROF(9);
            } else if (ISV) {
                bar_arrive(BAR_MEM, 512);
            }
            if (ISV && s >= 0) { xrows_o(s); PROF(10); }
        }
        bulk_wait0();
        PROF_DUMP();
        DONE();
        };
        if (wg == 2) {
            if (CFG) asm volatile("setmaxnreg.inc.sync.aligned.u32 144;"); else asm volatile("setmaxnreg.dec.sync.aligned.u32 112;");
            compute(TrueT{});
        } else {
            if (CFG) asm volatile("setmaxnreg.inc.sync.aligned.u32 160;"); else asm volatile("setmaxnreg.inc.sync.aligned.u32 176;");
            compute(FalseT{});
        }
    }
}

typedef CUresult (*EncodeFn)(CUtensorMap*, CUtensorMapDataType, cuuint32_t, void*, const cuuint64_t*, const cuuint64_t*,
                             const cuuint32_t*, const cuuint32_t*, CUtensorMapInterleave, CUtensorMapSwizzle,
                             CUtensorMapL2promotion, CUtensorMapFloatOOBfill);
#define DBG_SYNC(n)
#define USE_PDL 1
static int s_by_smid = 0;
static EncodeFn s_encode = nullptr;
#define CHECK_ENC(r) (void)(r)
static void make_map(CUtensorMap* m, const void* p, uint64_t cols, uint64_t rows, uint32_t bc, uint32_t br) {
    cuuint64_t dims[2] = {cols, rows};
    cuuint64_t strides[1] = {cols * 2};
    cuuint32_t box[2] = {bc, br};
    cuuint32_t es[2] = {1, 1};
    CUresult r = s_encode(m, CU_TENSOR_MAP_DATA_TYPE_BFLOAT16, 2, (void*)p, dims, strides, box, es, CU_TENSOR_MAP_INTERLEAVE_NONE,
             CU_TENSOR_MAP_SWIZZLE_128B, CU_TENSOR_MAP_L2_PROMOTION_L2_256B, CU_TENSOR_MAP_FLOAT_OOB_FILL_NONE);
    CHECK_ENC(r);
}

extern "C" void kernel_launch(void* const* d_in, const int* in_sizes, int n_in, void* d_out, int out_size) {
    const bf16* A_x = (const bf16*)d_in[0];
    const bf16* A_wqkv = (const bf16*)d_in[1];
    const bf16* A_wo = (const bf16*)d_in[2];
    const bf16* B_Wo = (const bf16*)d_in[8];
    if (!s_encode) {
        cudaDriverEntryPointQueryResult qr;
        cudaGetDriverEntryPoint("cuTensorMapEncodeTiled", (void**)&s_encode, cudaEnableDefault, &qr);
        cudaFuncSetAttribute(k1_qkv_gemm, cudaFuncAttributeMaxDynamicSharedMemorySize, K1_SMEM);
        cudaFuncSetAttribute(k3_attn, cudaFuncAttributeMaxDynamicSharedMemorySize, AT_SMEM);
        cudaFuncSetAttribute(k4_out_gemm, cudaFuncAttributeMaxDynamicSharedMemorySize, K4_SMEM);
        cudaFuncSetAttribute(k2_chain, cudaFuncAttributeMaxDynamicSharedMemorySize, CH_SMEM_ALL);
        int dev = 0, sms = 0;
        cudaGetDevice(&dev);
        cudaDeviceGetAttribute(&sms, cudaDevAttrMultiProcessorCount, dev);
        s_by_smid = sms == 132;
    }
    void *p_oA, *p_oB;
    cudaGetSymbolAddress(&p_oA, g_oA);
    cudaGetSymbolAddress(&p_oB, g_oB);
    CUtensorMap tmX, tmW, tmOA, tmWoA, tmOB, tmWoB, tmOut;
    make_map(&tmX, A_x, 1024, SEQ, 64, 256);
    make_map(&tmW, A_wqkv, 3072, 1024, 64, 64);
    make_map(&tmOA, p_oA, 1024, SEQ, 64, 128);
    make_map(&tmWoA, A_wo, 1024, 1024, 64, 64);
    make_map(&tmOB, p_oB, 4096, SEQ, 64, 128);
    make_map(&tmWoB, B_Wo, 1024, 4096, 64, 64);
    make_map(&tmOut, d_out, 2048, SEQ, 64, 64);
    CUtensorMap tmWq, tmWk, tmWv, tmXB;
    make_map(&tmWq, d_in[5], 4096, 1024, 64, 64);
    make_map(&tmWk, d_in[6], 4096, 1024, 64, 64);
    make_map(&tmWv, d_in[7], 4096, 1024, 64, 64);
    {
        cuuint64_t dims[3] = {64, SEQ, 16};
        cuuint64_t strides[2] = {2048, 128};
        cuuint32_t box[3] = {64, 32, 8};
        cuuint32_t es[3] = {1, 1, 1};
        CUresult r = s_encode(&tmXB, CU_TENSOR_MAP_DATA_TYPE_BFLOAT16, 3, d_in[3], dims, strides, box, es, CU_TENSOR_MAP_INTERLEAVE_NONE,
                              CU_TENSOR_MAP_SWIZZLE_128B, CU_TENSOR_MAP_L2_PROMOTION_L2_256B, CU_TENSOR_MAP_FLOAT_OOB_FILL_NONE);
        CHECK_ENC(r);
    }
    void* p_cb;
    cudaGetSymbolAddress(&p_cb, g_cb);
    p_cb = (void*)(((uintptr_t)p_cb + 65535) & ~(uintptr_t)65535);
    cudaStream_t st = cudaStreamPerThread;
    cudaLaunchAttribute at[1];
    at[0].id = cudaLaunchAttributeProgrammaticStreamSerialization;
    at[0].val.programmaticStreamSerializationAllowed = 1;
    cudaLaunchConfig_t cfg = {};
    cfg.stream = st;
    cfg.attrs = at;
    cfg.numAttrs = USE_PDL;
    k1_qkv_gemm<<<128, 384, K1_SMEM, st>>>(tmX, tmW, (uint4*)((char*)p_cb + CB_CLEAR_OFF), CB_CLEAR / 16, (uint4*)((char*)p_cb + G1_OFF));
    DBG_SYNC("k1");
    cfg.gridDim = dim3(128); cfg.blockDim = dim3(512); cfg.dynamicSmemBytes = AT_SMEM;
    cudaLaunchKernelEx(&cfg, k3_attn, tmWq, tmWk, tmWv, tmWoB, (const char*)d_in[3], s_by_smid);
    DBG_SYNC("k3");
    cfg.gridDim = dim3(132); cfg.blockDim = dim3(512); cfg.dynamicSmemBytes = CH_SMEM_ALL;
    cudaLaunchKernelEx(&cfg, k2_chain, tmWq, tmWk, tmWv, tmWoB, tmXB, tmOA, tmWoA, tmOut, (const bf16*)d_in[4], (char*)p_cb, 0u, s_by_smid);
    DBG_SYNC("k2");
    cfg.gridDim = dim3(128); cfg.blockDim = dim3(288); cfg.dynamicSmemBytes = K4_SMEM;
    cudaLaunchKernelEx(&cfg, k4_out_gemm, tmOB, tmWoB, tmOut);
}
```
